```python
import torch

def _softmax(x, axis=-1):
    return torch.softmax(x, dim=axis)
def _gelu(x):
    return torch.nn.functional.gelu(x, approximate="tanh")
def _silu(x):
    return torch.nn.functional.silu(x)
def _sigmoid(x):
    return torch.sigmoid(x)
def _layernorm(x, axis=-1, eps=1e-5):
    m = x.mean(dim=axis, keepdim=True)
    v = x.var(dim=axis, keepdim=True, unbiased=False)
    return (x - m) / torch.sqrt(v + eps)
def _scatter_add(tgt, idx, src, axis=0):
    return tgt.clone().index_add_(axis, idx, src)
def _segment_sum(src, seg, n):
    out = torch.zeros((n,) + src.shape[1:], dtype=src.dtype)
    return out.index_add_(0, seg, src)
def _pad(x, pw):
    flat = tuple(v for pair in reversed(pw) for v in pair)
    return torch.nn.functional.pad(x, flat)

kernel_name = 'recurrent_scan__mha_block_cached__swiglu_ffn__decode'

def setup_inputs():

    _w = (lambda a: (lambda t: t.to(torch.bfloat16) if t.is_floating_point() else t)(torch.as_tensor(a)))
    def _A_setup():
        B, Sq, D = 1, 1, 640
        H, Sk, Dh = 32, 4096, 192
        return {
            "x": _w((lambda *s: torch.randn(*s, dtype=torch.bfloat16) * 0.05)(B, Sq, D)),
            "k_cache": _w((lambda *s: torch.randn(*s, dtype=torch.bfloat16) * 1.6)(B, H, Sk, Dh)),
            "v_cache": _w((lambda *s: torch.randn(*s, dtype=torch.bfloat16) * 0.2)(B, H, Sk, Dh)),
            "wq": _w((lambda *s: torch.randn(*s, dtype=torch.bfloat16) * 1.6)(D, H * Dh) * (D ** -0.5)),
            "wo": _w((lambda *s: torch.randn(*s, dtype=torch.bfloat16) * 0.2)(H * Dh, D) * ((H * Dh) ** -0.5)),
        }
    _A_in = _A_setup()

    def _B_setup():
        B, S, D, F = 1, 1, 640, 1536
        return {
            "x": _w((lambda *s: torch.randn(*s, dtype=torch.bfloat16) * 0.05)(B, S, D)),
            "w_gate": _w((lambda *s: torch.randn(*s, dtype=torch.bfloat16) * 0.1)(D, F)),
            "w_up": _w((lambda *s: torch.randn(*s, dtype=torch.bfloat16) * 0.1)(D, F)),
            "w_down": _w((lambda *s: torch.randn(*s, dtype=torch.bfloat16) * 0.1)(F, D)),
        }
    _B_in = _B_setup()

    return {
        "A_x": _A_in["x"],
        "A_k_cache": _A_in["k_cache"],
        "A_v_cache": _A_in["v_cache"],
        "A_wq": _A_in["wq"],
        "A_wo": _A_in["wo"],
        "B_x": _B_in["x"],
        "B_w_gate": _B_in["w_gate"],
        "B_w_up": _B_in["w_up"],
        "B_w_down": _B_in["w_down"],
    }

def reference(A_x, A_k_cache, A_v_cache, A_wq, A_wo, B_x, B_w_gate, B_w_up, B_w_down):
    def _A_ref(x, k_cache, v_cache, wq, wo):
        B, Sq, D = x.shape
        H, Dh = 32, 192
        q = (lambda x, *d: x.permute(*d))((x @ wq).reshape(B, Sq, H, Dh), 0, 2, 1, 3)
        scores = torch.einsum("bhqd,bhkd->bhqk", q, k_cache) * (Dh ** -0.5)
        p = _softmax(scores, axis=-1)
        o = torch.einsum("bhqk,bhkd->bhqd", p, v_cache)
        return (lambda x, *d: x.permute(*d))(o, 0, 2, 1, 3).reshape(B, Sq, H * Dh) @ wo

    def _B_ref(x, w_gate, w_up, w_down):
        g = _silu(x @ w_gate)
        u = x @ w_up
        return (g * u) @ w_down

    x = A_x
    xn = _layernorm(x, axis=-1)
    s = _A_ref(xn, A_k_cache, A_v_cache, A_wq, A_wo)
    g = _silu(_B_ref(xn, B_w_gate, B_w_up, B_w_down))
    return x + s * g
```

```cpp
#include <cuda_runtime.h>
#include <cuda_bf16.h>
#include <cuda.h>
#include <stdint.h>

namespace {

constexpr int kH = 32, kSk = 4096, kDh = 192, kD = 640, kF = 1536;
constexpr int kAttnCtas = 128, kRedCtas = 4, kThreads = 320;
constexpr int kStageBytes = 24576, kStages = 9;
constexpr int kTiles = 16;
#define INFLIGHT_BYTES 65536
#define INFLIGHT_MID 98304
#define INFLIGHT_END INFLIGHT_MID
#define MID_FROM 10
#define END_FROM 36
#define FIRST_BURST 3

constexpr int kLdGate = 3, kLdK = 5, kLdDown = kLdK + kTiles, kLdV = kLdDown + 1;
constexpr int kLdWo = kLdV + kTiles, kLoads = kLdWo + 3;
constexpr int kFirstBurst = FIRST_BURST;

__host__ __device__ constexpr int load_bytes(int i) {
    return i < 2 ? kStageBytes : i == 2 ? kStageBytes / 2 : i < kLdK ? 160 * 96 : i == kLdDown ? 48 * 320
         : i >= kLdWo ? 64 * 320 : kStageBytes;
}
__host__ __device__ constexpr int loads_landed_before(int i) {
    int k = i, sum = load_bytes(i);
    const int cap = i < MID_FROM ? INFLIGHT_BYTES : i < END_FROM ? INFLIGHT_MID : INFLIGHT_END;
    while (k > 0 && sum + load_bytes(k - 1) <= cap) sum += load_bytes(--k);
    return k;
}
__host__ __device__ constexpr uint64_t landed_step_mask(int step) {
    uint64_t m = 0;
    int have = 0;
    for (int i = kFirstBurst; i < kLoads; i++) {
        const int need = loads_landed_before(i);
        if (need - have >= step) m |= 1ull << i;
        if (need > have) have = need;
    }
    return m;
}

constexpr int kOffScore = kStages * kStageBytes;
constexpr int kOffP = kOffScore + 4096;
constexpr int kOffXn = kOffP + 4096;
constexpr int kOffQ = kOffXn + 640;
constexpr int kOffHid = kOffQ + 768;
constexpr int kOffRed = kOffHid + 256;
constexpr int kOffBar = kOffRed + 32;
constexpr int kSmemBytes = kOffBar + 16 * kStages;

constexpr int kXPitch = 152;
constexpr unsigned kSpinLimit = 1u << 24;

struct Maps { CUtensorMap k, v, wq, gate, up, down, wo; };

__device__ uint4 g_x01[2 * kAttnCtas * kXPitch];
__device__ uint4 g_xout[2 * 40 * kH * 8];
__device__ unsigned g_epoch[kAttnCtas + kRedCtas];

#define TR(cond, id) do {} while (0)

__device__ __forceinline__ void mbar_init(uint32_t bar, uint32_t cnt) {
    asm volatile("mbarrier.init.shared::cta.b64 [%0], %1;" :: "r"(bar), "r"(cnt) : "memory");
}
__device__ __forceinline__ void mbar_expect_tx(uint32_t bar, uint32_t bytes) {
    asm volatile("mbarrier.arrive.expect_tx.shared::cta.b64 _, [%0], %1;" :: "r"(bar), "r"(bytes) : "memory");
}
__device__ __forceinline__ void mbar_arrive(uint32_t bar) {
    asm volatile("mbarrier.arrive.shared::cta.b64 _, [%0];" :: "r"(bar) : "memory");
}
__device__ __forceinline__ bool mbar_try(uint32_t bar, uint32_t parity) {
    uint32_t ok;
    asm volatile("{\n.reg .pred p;\nmbarrier.try_wait.parity.shared::cta.b64 p, [%1], %2;\nselp.u32 %0, 1, 0, p;\n}"
                 : "=r"(ok) : "r"(bar), "r"(parity) : "memory");
    return ok;
}
__device__ __forceinline__ void mbar_wait(uint32_t bar, uint32_t parity) {
    unsigned n = 0;
    while (!mbar_try(bar, parity)) { if (++n > kSpinLimit) __trap(); }
}
__device__ __forceinline__ void tma3(uint32_t dst, const CUtensorMap* tm, int c0, int c1, int c2, uint32_t bar, uint64_t pol) {
    asm volatile("cp.async.bulk.tensor.3d.shared::cluster.global.mbarrier::complete_tx::bytes.L2::cache_hint"
                 " [%0], [%1, {%3, %4, %5}], [%2], %6;"
                 :: "r"(dst), "l"(tm), "r"(bar), "r"(c0), "r"(c1), "r"(c2), "l"(pol) : "memory");
}
__device__ __forceinline__ void tma2(uint32_t dst, const CUtensorMap* tm, int c0, int c1, uint32_t bar, uint64_t pol) {
    asm volatile("cp.async.bulk.tensor.2d.shared::cluster.global.mbarrier::complete_tx::bytes.L2::cache_hint"
                 " [%0], [%1, {%3, %4}], [%2], %5;"
                 :: "r"(dst), "l"(tm), "r"(bar), "r"(c0), "r"(c1), "l"(pol) : "memory");
}
__device__ __forceinline__ void ldsm4(uint32_t (&a)[4], uint32_t addr) {
    asm volatile("ldmatrix.sync.aligned.m8n8.x4.shared.b16 {%0,%1,%2,%3}, [%4];"
                 : "=r"(a[0]), "=r"(a[1]), "=r"(a[2]), "=r"(a[3]) : "r"(addr) : "memory");
}
__device__ __forceinline__ void ldsm4t(uint32_t (&a)[4], uint32_t addr) {
    asm volatile("ldmatrix.sync.aligned.m8n8.x4.trans.shared.b16 {%0,%1,%2,%3}, [%4];"
                 : "=r"(a[0]), "=r"(a[1]), "=r"(a[2]), "=r"(a[3]) : "r"(addr) : "memory");
}
__device__ __forceinline__ void mma(float (&c)[4], const uint32_t (&a)[4], uint32_t b0, uint32_t b1) {
    asm("mma.sync.aligned.m16n8k16.row.col.f32.bf16.bf16.f32 {%0,%1,%2,%3}, {%4,%5,%6,%7}, {%8,%9}, {%0,%1,%2,%3};"
                 : "+f"(c[0]), "+f"(c[1]), "+f"(c[2]), "+f"(c[3])
                 : "r"(a[0]), "r"(a[1]), "r"(a[2]), "r"(a[3]), "r"(b0), "r"(b1));
}
__device__ __forceinline__ uint4 lds128(uint32_t addr) {
    uint4 v;
    asm volatile("ld.shared.v4.u32 {%0,%1,%2,%3}, [%4];" : "=r"(v.x), "=r"(v.y), "=r"(v.z), "=r"(v.w) : "r"(addr) : "memory");
    return v;
}
__device__ __forceinline__ void consumer_sync() { asm volatile("bar.sync 1, 128;" ::: "memory"); }

__device__ __forceinline__ void ll_store(uint4* p, float a, float b, unsigned tag) {
    const uint64_t w0 = ((uint64_t)tag << 32) | __float_as_uint(a);
    const uint64_t w1 = ((uint64_t)tag << 32) | __float_as_uint(b);
    asm volatile("st.relaxed.gpu.global.v2.b64 [%0], {%1, %2};" :: "l"(p), "l"(w0), "l"(w1) : "memory");
}
__device__ __forceinline__ void ll_poll(const uint4* p, unsigned tag, uint64_t& w0, uint64_t& w1) {
    asm volatile("{\n.reg .pred p;\n.reg .b32 lo, h0, h1;\n"
                 "mov.b64 {lo, h0}, %0;\nmov.b64 {lo, h1}, %1;\n"
                 "setp.ne.u32 p, h0, %3;\nsetp.ne.or.u32 p, h1, %3, p;\n"
                 "@p ld.relaxed.gpu.global.v2.b64 {%0, %1}, [%2];\n}"
                 : "+l"(w0), "+l"(w1) : "l"(p), "r"(tag) : "memory");
}
__device__ __forceinline__ void ll_gather8(const uint4* p0, const uint4* p1, int pitch, unsigned tag, unsigned sleep_ns,
                                           float (&a)[8], float (&b)[8]) {
    uint64_t w0[8], w1[8];
#pragma unroll
    for (int i = 0; i < 8; i++) w0[i] = w1[i] = (uint64_t)(~tag) << 32;
    for (unsigned n = 0;; n++) {
#pragma unroll
        for (int i = 0; i < 8; i++) ll_poll((i < 4 ? p0 : p1) + (i & 3) * pitch, tag, w0[i], w1[i]);
        uint32_t miss = 0;
#pragma unroll
        for (int i = 0; i < 8; i++) miss |= ((uint32_t)(w0[i] >> 32) ^ tag) | ((uint32_t)(w1[i] >> 32) ^ tag);
        if (miss == 0) break;
        if (n > kSpinLimit) __trap();
        if (sleep_ns) __nanosleep(sleep_ns);
    }
#pragma unroll
    for (int i = 0; i < 8; i++) { a[i] = __uint_as_float((uint32_t)w0[i]); b[i] = __uint_as_float((uint32_t)w1[i]); }
}
__device__ __forceinline__ void ll_gather2(const uint4* p0, const uint4* p1, unsigned tag, float (&a)[8], float (&b)[8]) {
    ll_gather8(p0, p1, kXPitch, tag, 0, a, b);
}

__device__ __forceinline__ float bf16r(float v) { return __bfloat162float(__float2bfloat16_rn(v)); }
__device__ __forceinline__ float bf_lo(uint32_t u) { return __uint_as_float(u << 16); }
__device__ __forceinline__ float bf_hi(uint32_t u) { return __uint_as_float(u & 0xffff0000u); }
__device__ __forceinline__ uint32_t pack_bf16(float lo, float hi) {
    __nv_bfloat162 t = __floats2bfloat162_rn(lo, hi);
    return *reinterpret_cast<uint32_t*>(&t);
}
__device__ __forceinline__ float silu(float v) { return __fdividef(v, 1.0f + __expf(-v)); }
__device__ __forceinline__ float pick3(int s, float a, float b, float c) { return s == 0 ? a : (s == 1 ? b : c); }

__device__ __forceinline__ int bvec_off(int mt, int r) {
    return (mt >> 1) * 128 + (r >> 1) * 16 + (mt & 1) * 8 + (r & 1) * 2;
}

struct Ring {
    uint32_t full, empty;
    int slot; uint32_t phase;
    __device__ __forceinline__ uint32_t acquire(uint32_t ring) {
        mbar_wait(full + 8 * slot, phase);
        return ring + slot * kStageBytes;
    }
    __device__ __forceinline__ void release(int lane) {
        __syncwarp();
        if (lane == 0) mbar_arrive(empty + 8 * slot);
        if (++slot == kStages) { slot = 0; phase ^= 1; }
    }
};

__device__ __forceinline__ void gemv384(float (&acc)[3][4], uint32_t tile, const uint32_t (&off)[3], uint32_t bvec) {
    const uint4 b = lds128(bvec);
    uint32_t a[2][3][4];
#pragma unroll
    for (int ks = 0; ks < 2; ks++)
#pragma unroll
        for (int m = 0; m < 3; m++) ldsm4t(a[ks][m], tile + off[m] + ks * (16 * 384));
#pragma unroll
    for (int m = 0; m < 3; m++) mma(acc[m], a[0][m], b.x, b.y);
#pragma unroll
    for (int m = 0; m < 3; m++) mma(acc[m], a[1][m], b.z, b.w);
}

__device__ __forceinline__ void gemv320(float (&acc)[3][4], uint32_t tile, const uint32_t (&off)[3], const uint4& b) {
    uint32_t a[2][3][4];
#pragma unroll
    for (int ks = 0; ks < 2; ks++)
#pragma unroll
        for (int m = 0; m < 3; m++) ldsm4t(a[ks][m], tile + off[m] + ks * (16 * 320));
#pragma unroll
    for (int m = 0; m < 3; m++) mma(acc[m], a[0][m], b.x, b.y);
#pragma unroll
    for (int m = 0; m < 3; m++) mma(acc[m], a[1][m], b.z, b.w);
}

__device__ __forceinline__ void zero3(float (&acc)[3][4]) {
#pragma unroll
    for (int m = 0; m < 3; m++)
#pragma unroll
        for (int i = 0; i < 4; i++) acc[m][i] = 0.f;
}

__device__ __forceinline__ void issue_wq(const Maps& maps, uint32_t sm, int i, int h, int j, uint64_t pol) {
    const uint32_t bar = sm + kOffBar + 8 * i, dst = sm + i * kStageBytes;
    const int row = j * 160 + i * 64;
    mbar_expect_tx(bar, load_bytes(i));
    tma3(dst, &maps.wq, 0, 3 * h, row, bar, pol);
    if (i < 2) tma3(dst + kStageBytes / 2, &maps.wq, 0, 3 * h, row + 32, bar, pol);
}

__device__ __forceinline__ void producer(const Maps& maps, uint32_t sm, int h, int j, uint64_t pol) {
    const uint32_t full = sm + kOffBar, empty = full + 8 * kStages;
    const int kvrow = h * kSk + j * (kTiles * 64);
    constexpr uint64_t m1 = landed_step_mask(1), m2 = landed_step_mask(2), m3 = landed_step_mask(3);
    int slot = 3; uint32_t phase = 1;
    int tslot = 0; uint32_t tphase = 0;
#pragma unroll 1
    for (int i = 3; i < kLoads; i++) {
        const uint32_t bar = full + 8 * slot, dst = sm + slot * kStageBytes;
        if (i >= kStages) mbar_wait(empty + 8 * slot, phase);
        const int steps = (int)((m1 >> i) & 1) + (int)((m2 >> i) & 1) + (int)((m3 >> i) & 1);
#pragma unroll 1
        for (int t = 0; t < steps; t++) {
            mbar_wait(full + 8 * tslot, tphase);
            if (++tslot == kStages) { tslot = 0; tphase ^= 1; }
        }
        const CUtensorMap* tm; int c1, c2; uint32_t bytes;
        if (i < kLdK) {
            mbar_expect_tx(bar, 160 * 96);
            tma2(dst, i == kLdGate ? &maps.gate : &maps.up, 48 * h, 160 * j, bar, pol);
        } else {
            if (i < kLdDown)       { tm = &maps.k;    c1 = 0;     c2 = kvrow + 64 * (i - kLdK);       bytes = kStageBytes; }
            else if (i == kLdDown) { tm = &maps.down; c1 = 5 * j; c2 = 48 * h;                        bytes = 48 * 320; }
            else if (i < kLdWo)    { tm = &maps.v;    c1 = 0;     c2 = kvrow + 64 * (i - kLdV);       bytes = kStageBytes; }
            else                   { tm = &maps.wo;   c1 = 5 * j; c2 = kDh * h + 64 * (i - kLdWo);    bytes = 64 * 320; }
            mbar_expect_tx(bar, bytes);
            tma3(dst, tm, 0, c1, c2, bar, pol);
        }
        if (++slot == kStages) { slot = 0; phase ^= 1; }
    }
    TR(true, 2);
}

__device__ __forceinline__ void consumer(const __nv_bfloat16* __restrict__ x, uint8_t* smem, uint32_t sm, int h, int j) {
    const int tid = threadIdx.x, lane = tid & 31, w = tid >> 5;
    const int quad = lane & 3, r = lane >> 2;
    const int cta = blockIdx.x;

    const uint4* x4 = reinterpret_cast<const uint4*>(x);
    uint4 xv[3];
    xv[0] = __ldg(x4 + lane);
    xv[1] = __ldg(x4 + 32 + lane);
    xv[2] = lane < 16 ? __ldg(x4 + 64 + lane) : make_uint4(0, 0, 0, 0);
    uint32_t xs = 0;
    if (tid < 80) xs = __ldg(reinterpret_cast<const uint32_t*>(x) + j * 80 + tid);
    unsigned epoch = __ldcg(&g_epoch[cta]) + 1;

    for (int i = tid; i < (kOffRed - kOffXn) / 16; i += 128)
        *reinterpret_cast<uint4*>(smem + kOffXn + i * 16) = make_uint4(0, 0, 0, 0);

    float sum = 0.f;
#pragma unroll
    for (int i = 0; i < 3; i++) {
        const uint32_t u[4] = {xv[i].x, xv[i].y, xv[i].z, xv[i].w};
#pragma unroll
        for (int k = 0; k < 4; k++) sum += bf_lo(u[k]) + bf_hi(u[k]);
    }
#pragma unroll
    for (int s = 16; s > 0; s >>= 1) sum += __shfl_xor_sync(~0u, sum, s);
    const float mean = sum * (1.0f / kD);
    float sq = 0.f;
#pragma unroll
    for (int i = 0; i < 3; i++) {
        const uint32_t u[4] = {xv[i].x, xv[i].y, xv[i].z, xv[i].w};
        if (i < 2 || lane < 16) {
#pragma unroll
            for (int k = 0; k < 4; k++) {
                const float a = bf_lo(u[k]) - mean, b = bf_hi(u[k]) - mean;
                sq += a * a + b * b;
            }
        }
    }
#pragma unroll
    for (int s = 16; s > 0; s >>= 1) sq += __shfl_xor_sync(~0u, sq, s);
    const float mean_b = bf16r(mean);
    const float den = bf16r(__fsqrt_rn(bf16r(bf16r(sq * (1.0f / kD)) + 1e-5f)));
    consumer_sync();
    if (tid == 0) g_epoch[cta] = epoch;
    if (tid < 80) {
        const int k = 2 * tid;
        const float a = __fdividef(bf16r(bf_lo(xs) - mean_b), den), b = __fdividef(bf16r(bf_hi(xs) - mean_b), den);
        const int off = (k >> 5) * 128 + ((k & 7) >> 1) * 16 + ((k >> 4) & 1) * 8 + ((k >> 3) & 1) * 4;
        *reinterpret_cast<uint32_t*>(smem + kOffXn + off) = pack_bf16(a, b);
    }
    asm volatile("bar.sync 2, 160;" ::: "memory");
    TR(tid == 0, 3);

    Ring ring{sm + kOffBar, sm + kOffBar + 8 * kStages, 0, 0};
    const int mi = lane >> 3, lr = lane & 7;
    const uint32_t bsel = (r & 1) * 64 + quad * 16;

    uint32_t off384[3];
    {
        const int row = (mi >> 1) * 8 + lr;
#pragma unroll
        for (int m = 0; m < 3; m++) {
            const int chunk = 2 * (3 * w + m) + (mi & 1), seg = chunk >> 3;
            off384[m] = row * 384 + seg * 128 + (((chunk & 7) ^ ((3 * row + seg) & 7)) << 4);
        }
    }
    uint32_t off320[3];
    {
        const int row = (mi >> 1) * 8 + lr;
#pragma unroll
        for (int m = 0; m < 3; m++) {
            const int mt = w + 4 * m < 10 ? w + 4 * m : w;
            const uint32_t lin = row * 320 + (2 * mt + (mi & 1)) * 16;
            off320[m] = lin ^ (((lin >> 7) & 3) << 4);
        }
    }
    const bool third = w < 2;
    float* score = reinterpret_cast<float*>(smem + kOffScore);
    float* red = reinterpret_cast<float*>(smem + kOffRed);
    float mx = 0.f;
    float acc[3][4];

#pragma unroll 1
    for (int pass = 0; pass < 2; pass++) {
        zero3(acc);
        {
            const int halves = pass ? 2 * kTiles : 5;
            uint32_t bv = sm + (pass ? kOffP : kOffXn) + bsel;
#pragma unroll 1
            for (int t = 0; t < halves; t += 2) {
                const uint32_t tile = ring.acquire(sm);
                gemv384(acc, tile, off384, bv);
                if (t + 1 < halves) gemv384(acc, tile + 32 * 384, off384, bv + 128);
                ring.release(lane);
                bv += 256;
            }
        }
        TR(tid == 0, pass ? 9 : 4);
        uint4* xmine = g_x01 + (pass * kAttnCtas + cta) * kXPitch;
        if (quad < 3)
            ll_store(xmine + (3 * w + quad) * 8 + r,
                     pick3(quad, acc[0][0] + acc[0][1], acc[1][0] + acc[1][1], acc[2][0] + acc[2][1]),
                     pick3(quad, acc[0][2] + acc[0][3], acc[1][2] + acc[1][3], acc[2][2] + acc[2][3]), epoch);
        else if (tid == 3)
            ll_store(xmine + 96, mx, pass ? (red[4] + red[5]) + (red[6] + red[7]) : 0.25f, epoch);

        const uint4* xgrp = g_x01 + (pass * kAttnCtas + (cta & ~3)) * kXPitch;
        if (pass == 0) {
            zero3(acc);
            const uint32_t off96 = ((mi >> 1) * 8 + lr) * 96 + (2 * w + (mi & 1)) * 16;
#pragma unroll 1
            for (int g = 0; g < 2; g++) {
                const uint32_t tile = ring.acquire(sm);
                if (w < 3) {
                    float c[4] = {0.f, 0.f, 0.f, 0.f};
#pragma unroll
                    for (int kb = 0; kb < 5; kb++) {
                        const uint4 b = lds128(sm + kOffXn + kb * 128 + bsel);
                        uint32_t a0[4], a1[4];
                        ldsm4t(a0, tile + off96 + kb * (32 * 96));
                        ldsm4t(a1, tile + off96 + kb * (32 * 96) + 16 * 96);
                        mma(c, a0, b.x, b.y);
                        mma(c, a1, b.z, b.w);
                    }
                    if (quad == 0) ll_store(xmine + 104 + g * 24 + w * 8 + r, c[0], c[2], epoch);
                }
                ring.release(lane);
            }
            TR(tid == 0, 5);
        }

        if (tid < 96) {
            float a[8], b[8];
            ll_gather2(xgrp + tid, xgrp + 96, epoch, a, b);
            const float gm = fmaxf(fmaxf(a[4], a[5]), fmaxf(a[6], a[7]));
            float dn = 0.f, o0 = 0.f, o1 = 0.f;
#pragma unroll
            for (int i = 0; i < 4; i++) {
                const float e = __expf(a[4 + i] - gm);
                dn += e * b[4 + i]; o0 += e * a[i]; o1 += e * b[i];
            }
            __nv_bfloat16* dst = reinterpret_cast<__nv_bfloat16*>(smem + kOffQ + bvec_off(tid >> 3, tid & 7));
            dst[0] = __float2bfloat16_rn(__fdividef(o0, dn));
            dst[2] = __float2bfloat16_rn(__fdividef(o1, dn));
        } else if (pass == 0 && tid < 120) {
            const int u = tid - 96;
            float a[8], b[8];
            ll_gather2(xgrp + 104 + u, xgrp + 128 + u, epoch, a, b);
            const float g0 = bf16r(silu(bf16r((a[0] + a[1]) + (a[2] + a[3]))));
            const float g1 = bf16r(silu(bf16r((b[0] + b[1]) + (b[2] + b[3]))));
            __nv_bfloat16* dst = reinterpret_cast<__nv_bfloat16*>(smem + kOffHid + bvec_off((u >> 3) + (u >> 4), u & 7));
            dst[0] = __float2bfloat16_rn(g0 * bf16r((a[4] + a[5]) + (a[6] + a[7])));
            dst[2] = __float2bfloat16_rn(g1 * bf16r((b[4] + b[5]) + (b[6] + b[7])));
        }
        consumer_sync();
        TR(tid == 0, pass ? 10 : 6);

        if (pass == 0) {
            uint32_t qf[24];
#pragma unroll
            for (int kb = 0; kb < 6; kb++) {
                const uint4 b = lds128(sm + kOffQ + kb * 128 + quad * 16);
                qf[4 * kb] = b.x; qf[4 * kb + 1] = b.y; qf[4 * kb + 2] = b.z; qf[4 * kb + 3] = b.w;
            }
            const int row = 16 * w + (mi & 1) * 8 + lr;
            uint32_t offk[3];
#pragma unroll
            for (int seg = 0; seg < 3; seg++)
                offk[seg] = row * 384 + seg * 128 + (((mi >> 1) ^ ((3 * row + seg) & 7)) << 4);
            const float scale = 0.07216878364870323f;
            mx = -INFINITY;
#pragma unroll 1
            for (int t = 0; t < kTiles; t++) {
                const uint32_t tile = ring.acquire(sm);
                float c0[4] = {0.f, 0.f, 0.f, 0.f}, c1[4] = {0.f, 0.f, 0.f, 0.f};
                uint32_t a[12][4];
#pragma unroll
                for (int ks = 0; ks < 12; ks++) ldsm4(a[ks], tile + (offk[ks >> 2] ^ ((ks & 3) << 5)));
#pragma unroll
                for (int ks = 0; ks < 12; ks += 2) {
                    mma(c0, a[ks], qf[2 * ks], qf[2 * ks + 1]);
                    mma(c1, a[ks + 1], qf[2 * ks + 2], qf[2 * ks + 3]);
                }
                ring.release(lane);
                const float s = bf16r(bf16r((quad & 1) ? c0[2] + c1[2] : c0[0] + c1[0]) * scale);
                mx = fmaxf(mx, s);
                if (quad < 2) score[t * 64 + 16 * w + quad * 8 + r] = s;
            }
#pragma unroll
            for (int s = 16; s > 0; s >>= 1) mx = fmaxf(mx, __shfl_xor_sync(~0u, mx, s));
            if (lane == 0) red[w] = mx;
            consumer_sync();
            TR(tid == 0, 7);
            mx = fmaxf(fmaxf(red[0], red[1]), fmaxf(red[2], red[3]));

            float lsum = 0.f;
            const int blk = tid >> 2;
            uint32_t hi[4], lo[4];
#pragma unroll
            for (int i = 0; i < 4; i++) {
                const float2 s = *reinterpret_cast<const float2*>(score + blk * 32 + i * 8 + 2 * quad);
                const float e0 = __expf(s.x - mx), e1 = __expf(s.y - mx);
                lsum += e0 + e1;
                hi[i] = pack_bf16(e0, e1);
                lo[i] = pack_bf16(e0 - bf_lo(hi[i]), e1 - bf_hi(hi[i]));
            }
            *reinterpret_cast<uint4*>(smem + kOffP + blk * 128 + quad * 16) = make_uint4(hi[0], hi[1], hi[2], hi[3]);
            *reinterpret_cast<uint4*>(smem + kOffP + blk * 128 + 64 + quad * 16) = make_uint4(lo[0], lo[1], lo[2], lo[3]);
#pragma unroll
            for (int s = 16; s > 0; s >>= 1) lsum += __shfl_xor_sync(~0u, lsum, s);
            if (lane == 0) red[4 + w] = lsum;
        }

        zero3(acc);
        {
            uint32_t bv = sm + (pass ? kOffQ : kOffHid) + bsel;
            const int tiles = pass ? 3 : 1;
#pragma unroll 1
            for (int t = 0; t < tiles; t++) {
                const uint4 b0 = lds128(bv), b1 = lds128(bv + 128);
                const uint32_t tile = ring.acquire(sm);
                TR(tid == 0 && pass, 13 + t);
                gemv320(acc, tile, off320, b0);
                gemv320(acc, tile + (pass ? 32 * 320 : 16 * 320), off320, b1);
                ring.release(lane);
                bv += 256;
            }
        }
        TR(tid == 0 && pass, 11);
        if (quad < 2 || (quad == 2 && third))
            ll_store(g_xout + ((pass * 40 + j * 10 + w + 4 * quad) * kH + h) * 8 + r,
                     pick3(quad, acc[0][0], acc[1][0], acc[2][0]), pick3(quad, acc[0][2], acc[1][2], acc[2][2]), epoch);
        TR(tid == 0 && pass, 12);
        if (pass == 0) consumer_sync();
        TR(tid == 0 && !pass, 8);
    }
}

__device__ __forceinline__ void reducer(const __nv_bfloat16* __restrict__ x, __nv_bfloat16* __restrict__ out) {
    const int lane = threadIdx.x & 31, slot = (blockIdx.x - kAttnCtas) * 10 + (threadIdx.x >> 5);
    const unsigned epoch = __ldcg(&g_epoch[blockIdx.x]) + 1;
    const int col = slot * 16 + (lane & 15);
    const float xin = __bfloat162float(x[col]);
    __syncthreads();
    if (threadIdx.x == 0) g_epoch[blockIdx.x] = epoch;
    float g = 0.f;
#pragma unroll 1
    for (int pass = 0; pass < 2; pass++) {
        const uint4* src = g_xout + (pass * 40 + slot) * (kH * 8) + lane;
        float a[8], b[8];
        ll_gather8(src, src + 128, 32, epoch, pass ? 0 : 256, a, b);
        float s0 = ((a[0] + a[1]) + (a[2] + a[3])) + ((a[4] + a[5]) + (a[6] + a[7]));
        float s1 = ((b[0] + b[1]) + (b[2] + b[3])) + ((b[4] + b[5]) + (b[6] + b[7]));
        __syncwarp();
        s0 += __shfl_xor_sync(~0u, s0, 8);
        s1 += __shfl_xor_sync(~0u, s1, 8);
        s0 += __shfl_xor_sync(~0u, s0, 16);
        s1 += __shfl_xor_sync(~0u, s1, 16);
        const float v = bf16r((lane & 8) ? s1 : s0);
        if (pass && lane < 16) out[col] = __float2bfloat16_rn(xin + bf16r(v * g));
        g = bf16r(silu(v));
        TR(lane == 0, pass ? 16 + (threadIdx.x >> 5) : 8);
    }
}

__global__ void __launch_bounds__(kThreads, 1)
decode_block_kernel(const __grid_constant__ Maps maps, const __nv_bfloat16* __restrict__ x, __nv_bfloat16* __restrict__ out) {
    extern __shared__ __align__(1024) uint8_t smem[];
    const uint32_t sm = (uint32_t)__cvta_generic_to_shared(smem);
    const int w = threadIdx.x >> 5;
    const int h = blockIdx.x >> 2, j = blockIdx.x & 3;
    TR(threadIdx.x == 0, 0);
    uint64_t pol;
    asm volatile("createpolicy.fractional.L2::evict_first.b64 %0, 1.0;" : "=l"(pol));
    if (threadIdx.x == 128 && blockIdx.x < kAttnCtas) {
#pragma unroll
        for (int i = 0; i < kStages; i++) {
            mbar_init(sm + kOffBar + 8 * i, 1);
            mbar_init(sm + kOffBar + 8 * (kStages + i), 4);
        }
        asm volatile("fence.mbarrier_init.release.cluster;" ::: "memory");
        issue_wq(maps, sm, 0, h, j, pol);
        TR(true, 1);
        issue_wq(maps, sm, 1, h, j, pol);
        issue_wq(maps, sm, 2, h, j, pol);
    }
    __syncwarp();
    if (blockIdx.x >= kAttnCtas) { reducer(x, out); return; }
    if (w == 4) {
        asm volatile("bar.arrive 2, 160;" ::: "memory");
        if (threadIdx.x == 128) producer(maps, sm, h, j, pol);
    } else if (w < 4) {
        consumer(x, smem, sm, h, j);
    }
}

typedef CUresult (*EncodeFn)(CUtensorMap*, CUtensorMapDataType, cuuint32_t, void*, const cuuint64_t*, const cuuint64_t*,
                             const cuuint32_t*, const cuuint32_t*, CUtensorMapInterleave, CUtensorMapSwizzle,
                             CUtensorMapL2promotion, CUtensorMapFloatOOBfill);

void encode3(EncodeFn enc, CUtensorMap* tm, const void* p, uint64_t rows, uint64_t cols, uint32_t inner, uint32_t segs,
             uint32_t box_rows, CUtensorMapSwizzle sw) {
    const cuuint64_t dims[3] = {inner, cols / inner, rows};
    const cuuint64_t strides[2] = {inner * 2ull, cols * 2ull};
    const cuuint32_t box[3] = {inner, segs, box_rows};
    const cuuint32_t es[3] = {1, 1, 1};
    enc(tm, CU_TENSOR_MAP_DATA_TYPE_BFLOAT16, 3, const_cast<void*>(p), dims, strides, box, es,
        CU_TENSOR_MAP_INTERLEAVE_NONE, sw, CU_TENSOR_MAP_L2_PROMOTION_NONE, CU_TENSOR_MAP_FLOAT_OOB_FILL_NONE);
}
void encode2(EncodeFn enc, CUtensorMap* tm, const void* p, uint64_t rows, uint64_t cols, uint32_t box_cols, uint32_t box_rows) {
    const cuuint64_t dims[2] = {cols, rows};
    const cuuint64_t strides[1] = {cols * 2ull};
    const cuuint32_t box[2] = {box_cols, box_rows};
    const cuuint32_t es[2] = {1, 1};
    enc(tm, CU_TENSOR_MAP_DATA_TYPE_BFLOAT16, 2, const_cast<void*>(p), dims, strides, box, es,
        CU_TENSOR_MAP_INTERLEAVE_NONE, CU_TENSOR_MAP_SWIZZLE_NONE, CU_TENSOR_MAP_L2_PROMOTION_NONE,
        CU_TENSOR_MAP_FLOAT_OOB_FILL_NONE);
}

}

extern "C" void kernel_launch(void* const* d_in, const int* in_sizes, int n_in, void* d_out, int out_size) {
    (void)in_sizes; (void)n_in; (void)out_size;
    static EncodeFn enc = nullptr;
    if (!enc) {
        void* fn = nullptr;
        cudaDriverEntryPointQueryResult qr;
        cudaGetDriverEntryPoint("cuTensorMapEncodeTiled", &fn, cudaEnableDefault, &qr);
        enc = (EncodeFn)fn;
        cudaFuncSetAttribute(decode_block_kernel, cudaFuncAttributeMaxDynamicSharedMemorySize, kSmemBytes);
    }
    Maps maps;
    encode3(enc, &maps.k, d_in[1], (uint64_t)kH * kSk, kDh, 64, 3, 64, CU_TENSOR_MAP_SWIZZLE_128B);
    encode3(enc, &maps.v, d_in[2], (uint64_t)kH * kSk, kDh, 64, 3, 64, CU_TENSOR_MAP_SWIZZLE_128B);
    encode3(enc, &maps.wq, d_in[3], kD, kH * kDh, 64, 3, 32, CU_TENSOR_MAP_SWIZZLE_128B);
    encode3(enc, &maps.wo, d_in[4], kH * kDh, kD, 32, 5, 64, CU_TENSOR_MAP_SWIZZLE_64B);
    encode2(enc, &maps.gate, d_in[6], kD, kF, 48, 160);
    encode2(enc, &maps.up, d_in[7], kD, kF, 48, 160);
    encode3(enc, &maps.down, d_in[8], kF, kD, 32, 5, 48, CU_TENSOR_MAP_SWIZZLE_64B);
    decode_block_kernel<<<kAttnCtas + kRedCtas, kThreads, kSmemBytes>>>(
        maps, (const __nv_bfloat16*)d_in[0], (__nv_bfloat16*)d_out);
}
```

```cpp
#include <cuda_runtime.h>
#include <cuda_bf16.h>
#include <cuda.h>
#include <stdint.h>

namespace {

#define WINDOW_UNITS 192
#define WINDOW_END 128
#define START_BOOST 0
#define BOOST_UNTIL 7
#define END_FROM 37
#define GATE_TILE(h) (2 * ((h) >> 2) + 1)
#define WQ32 1
#define PREFETCH2 2
#define DOWN0 0
#define DOWN1 0
#define Q_DELAY 600
#define Q_SLEEP 500
#define O_DELAY 0
#define O_SLEEP 0
#define ALIAS_O 0
#define NO_CLEAR 0
#define HID_DELAY 3000
#define RAMP 0
#define RAMP_STEP 0
#define WO_STEP 0
#define WO2_FLAT 192
#define WO2_C 16
#define O_SPIN 1000
#define PROMO_ALL 0
#define PROMO_DOWN 3
#define PROMO_GATE 0
#define STAGGER_UNITS 192

constexpr int kH = 32, kSk = 4096, kDh = 192, kD = 640, kF = 1536;
constexpr int kCtas = 128, kThreads = 512;
constexpr int kFinishers = kD / 16, kFirstFinisher = kCtas - kFinishers;
constexpr int kStageBytes = 24576, kStages = 9;
constexpr int kTiles = 16;
constexpr int kLdGate = 3, kLdK = 5, kLdV = kLdK + kTiles, kLdWo = kLdV + kTiles;
constexpr int kLdDown = kLdWo + 3, kLoads = kLdDown + 2;

__host__ __device__ constexpr int load_bytes(int i) {
    return i == 2 ? kStageBytes / 2 : i >= kLdGate && i < kLdK ? 160 * 96 : i >= kLdWo && i < kLdDown ? 64 * 320 : kStageBytes;
}
constexpr int kUnit = 512, kWindow = WINDOW_UNITS, kStagger = STAGGER_UNITS;
__host__ __device__ constexpr int units_through(int i) {
    int sum = 0;
    for (int k = 0; k <= i; k++) sum += load_bytes(k) / kUnit;
    return sum;
}
constexpr int kLaunchUnits = 1 << 18;
constexpr int kPadUnits = kLaunchUnits - kCtas * units_through(kLdDown - 1) - kFinishers * 2 * (kStageBytes / kUnit);
static_assert(kPadUnits >= 0, "padding");

constexpr int kOffScore = kStages * kStageBytes;
constexpr int kOffP = kOffScore + 4096;
constexpr int kOffXn = kOffP + 4096;
constexpr int kOffQ = kOffXn + 640;
constexpr int kOffSend = kOffQ + 768;
constexpr int kOffRed = kOffSend + 192;
constexpr int kOffBar = kOffRed + 48;
constexpr int kOffVecBar = kOffBar + 16 * kStages;
constexpr int kOffPartBar = kOffVecBar + 8;
constexpr int kSmemBytes = kOffPartBar + 8;
constexpr int kOffHid = kOffScore;
constexpr int kOffPart = kOffHid + 2 * kF;

constexpr int kBoxQ = -192, kBoxO = 384, kBoxFfn = 1152, kBoxStat = 1536, kBoxWords = 1568;
constexpr unsigned kSpinLimit = 1u << 24;

constexpr int kBarMain = 1, kBarInit = 2, kBarMonitor = 3, kBarStat = 4, kBarGate = 5, kBarScale = 6, kBarProj = 7;

struct Maps { CUtensorMap wq, wq_tail, gate, up, k, v, down, wo; };

__device__ __align__(128) uint32_t g_box[kCtas * kBoxWords];
__device__ __align__(128) uint32_t g_hid[kFinishers * kF];
__device__ __align__(128) uint32_t g_out[kFinishers * kH * 16];
__device__ __align__(128) uint32_t g_sink[kH * 16];
__device__ __align__(128) unsigned g_landed[32];

#define TR(cond, id) do {} while (0)

__device__ __forceinline__ void mbar_init(uint32_t bar, uint32_t cnt) {
    asm volatile("mbarrier.init.shared::cta.b64 [%0], %1;" :: "r"(bar), "r"(cnt) : "memory");
}
__device__ __forceinline__ void mbar_expect_tx(uint32_t bar, uint32_t bytes) {
    asm volatile("mbarrier.arrive.expect_tx.shared::cta.b64 _, [%0], %1;" :: "r"(bar), "r"(bytes) : "memory");
}
__device__ __forceinline__ void mbar_arrive(uint32_t bar) {
    asm volatile("mbarrier.arrive.shared::cta.b64 _, [%0];" :: "r"(bar) : "memory");
}
__device__ __forceinline__ bool mbar_try(uint32_t bar, uint32_t parity) {
    uint32_t ok;
    asm volatile("{\n.reg .pred p;\nmbarrier.try_wait.parity.shared::cta.b64 p, [%1], %2;\nselp.u32 %0, 1, 0, p;\n}"
                 : "=r"(ok) : "r"(bar), "r"(parity) : "memory");
    return ok;
}
__device__ __forceinline__ bool mbar_test(uint32_t bar, uint32_t parity) {
    uint32_t ok;
    asm volatile("{\n.reg .pred p;\nmbarrier.test_wait.parity.shared::cta.b64 p, [%1], %2;\nselp.u32 %0, 1, 0, p;\n}"
                 : "=r"(ok) : "r"(bar), "r"(parity) : "memory");
    return ok;
}
__device__ __forceinline__ void mbar_wait(uint32_t bar, uint32_t parity) {
    unsigned n = 0;
    while (!mbar_try(bar, parity)) { if (++n > kSpinLimit) __trap(); }
}
__device__ __forceinline__ void tma3(uint32_t dst, const CUtensorMap* tm, int c0, int c1, int c2, uint32_t bar, uint64_t pol) {
    asm volatile("cp.async.bulk.tensor.3d.shared::cluster.global.mbarrier::complete_tx::bytes.L2::cache_hint"
                 " [%0], [%1, {%3, %4, %5}], [%2], %6;"
                 :: "r"(dst), "l"(tm), "r"(bar), "r"(c0), "r"(c1), "r"(c2), "l"(pol) : "memory");
}
__device__ __forceinline__ void ldsm4(uint32_t (&a)[4], uint32_t addr) {
    asm volatile("ldmatrix.sync.aligned.m8n8.x4.shared.b16 {%0,%1,%2,%3}, [%4];"
                 : "=r"(a[0]), "=r"(a[1]), "=r"(a[2]), "=r"(a[3]) : "r"(addr) : "memory");
}
__device__ __forceinline__ void ldsm4t(uint32_t (&a)[4], uint32_t addr) {
    asm volatile("ldmatrix.sync.aligned.m8n8.x4.trans.shared.b16 {%0,%1,%2,%3}, [%4];"
                 : "=r"(a[0]), "=r"(a[1]), "=r"(a[2]), "=r"(a[3]) : "r"(addr) : "memory");
}
__device__ __forceinline__ void mma(float (&c)[4], const uint32_t (&a)[4], uint32_t b0, uint32_t b1) {
    asm("mma.sync.aligned.m16n8k16.row.col.f32.bf16.bf16.f32 {%0,%1,%2,%3}, {%4,%5,%6,%7}, {%8,%9}, {%0,%1,%2,%3};"
                 : "+f"(c[0]), "+f"(c[1]), "+f"(c[2]), "+f"(c[3])
                 : "r"(a[0]), "r"(a[1]), "r"(a[2]), "r"(a[3]), "r"(b0), "r"(b1));
}
__device__ __forceinline__ uint4 lds128(uint32_t addr) {
    uint4 v;
    asm volatile("ld.shared.v4.u32 {%0,%1,%2,%3}, [%4];" : "=r"(v.x), "=r"(v.y), "=r"(v.z), "=r"(v.w) : "r"(addr) : "memory");
    return v;
}
__device__ __forceinline__ void lds128_if(uint4& v, uint32_t addr, uint32_t p) {
    asm volatile("{\n.reg .pred p;\nsetp.ne.u32 p, %5, 0;\n@p ld.shared.v4.u32 {%0,%1,%2,%3}, [%4];\n}"
                 : "+r"(v.x), "+r"(v.y), "+r"(v.z), "+r"(v.w) : "r"(addr), "r"(p) : "memory");
}
__device__ __forceinline__ void pin(uint32_t& v) { asm volatile("" : "+r"(v)); }
__device__ __forceinline__ void pin(float& v) { asm volatile("" : "+f"(v)); }
template <typename T> __device__ __forceinline__ void pin(T*& p) { asm volatile("" : "+l"(p)); }
template <int kId, int kCount> __device__ __forceinline__ void bar_sync() {
    asm volatile("bar.sync %0, %1;" :: "n"(kId), "n"(kCount) : "memory");
}
template <int kId, int kCount> __device__ __forceinline__ void bar_arrive() {
    asm volatile("bar.arrive %0, %1;" :: "n"(kId), "n"(kCount) : "memory");
}

__device__ __forceinline__ uint32_t tagged(float v) { return __float_as_uint(v) | 1u; }
__device__ __forceinline__ float untagged(uint32_t w) { return __uint_as_float(w & ~1u); }
__device__ __forceinline__ void put2(uint32_t* p, uint32_t a, uint32_t b) {
    asm volatile("st.relaxed.gpu.global.b64 [%0], %1;" :: "l"(p), "l"(((uint64_t)b << 32) | a) : "memory");
}
__device__ __forceinline__ void put2_if(uint32_t* p, uint32_t a, uint32_t b, uint32_t pred) {
    asm volatile("{\n.reg .pred p;\nsetp.ne.u32 p, %2, 0;\n@p st.relaxed.gpu.global.b64 [%0], %1;\n}"
                 :: "l"(p), "l"(((uint64_t)b << 32) | a), "r"(pred) : "memory");
}
__device__ __forceinline__ void put4(uint32_t* p, uint32_t a, uint32_t b, uint32_t c, uint32_t d) {
    asm volatile("st.relaxed.gpu.global.v4.b32 [%0], {%1, %2, %3, %4};" :: "l"(p), "r"(a), "r"(b), "r"(c), "r"(d) : "memory");
}
__device__ __forceinline__ void take(uint32_t* p, uint32_t& w) {
    asm volatile("atom.relaxed.gpu.global.exch.b32 %0, [%1], 0;" : "=r"(w) : "l"(p) : "memory");
}
__device__ __forceinline__ void take(uint32_t* p, uint64_t& w) {
    asm volatile("atom.relaxed.gpu.global.exch.b64 %0, [%1], 0;" : "=l"(w) : "l"(p) : "memory");
}
template <typename Word, int kN, typename Addr>
__device__ __forceinline__ void gather(Addr addr, Word (&w)[kN], unsigned mask, unsigned sleep_ns = 0, uint32_t init = 0) {
#pragma unroll
    for (int i = 0; i < kN; i++) w[i] = init;
    for (unsigned n = 0;; n++) {
        Word t[kN];
#pragma unroll
        for (int i = 0; i < kN; i++) take(addr(i), t[i]);
        uint32_t have = ~0u;
#pragma unroll
        for (int i = 0; i < kN; i++) {
            w[i] |= t[i];
            have &= (uint32_t)w[i];
        }
        pin(have);
        if (__all_sync(mask, have & 1)) {
            break;
        }
        if (n > kSpinLimit) __trap();
        if (sleep_ns) __nanosleep(sleep_ns);
    }
}
__device__ __forceinline__ void peek(const uint32_t* p, uint32_t& w) {
    asm volatile("{\n.reg .pred p;\n.reg .b32 t;\n"
                 "and.b32 t, %0, 1;\nsetp.eq.u32 p, t, 0;\n"
                 "@p ld.relaxed.gpu.global.b32 %0, [%1];\n}"
                 : "+r"(w) : "l"(p) : "memory");
}
__device__ __forceinline__ uint32_t clock_lo() {
    uint32_t c;
    asm volatile("mov.u32 %0, %%clock;" : "=r"(c) :: "memory");
    return c;
}
__device__ __forceinline__ void spin(uint32_t cycles) {
    const uint32_t start = clock_lo();
    while (clock_lo() - start < cycles) {}
}

__device__ __forceinline__ float bf16r(float v) { return __bfloat162float(__float2bfloat16_rn(v)); }
__device__ __forceinline__ float bf_lo(uint32_t u) { return __uint_as_float(u << 16); }
__device__ __forceinline__ float bf_hi(uint32_t u) { return __uint_as_float(u & 0xffff0000u); }
__device__ __forceinline__ uint32_t pack_bf16(float lo, float hi) {
    __nv_bfloat162 t = __floats2bfloat162_rn(lo, hi);
    return *reinterpret_cast<uint32_t*>(&t);
}
__device__ __forceinline__ float silu(float v) { return __fdividef(v, 1.0f + __expf(-v)); }
__device__ __forceinline__ float pick3(int s, float a, float b, float c) { return s == 0 ? a : (s == 1 ? b : c); }

__device__ __forceinline__ int bvec_off(int mt, int r) {
    return (mt >> 1) * 128 + (r >> 1) * 16 + (mt & 1) * 8 + (r & 1) * 2;
}

struct Ring {
    uint32_t full, empty;
    int slot; uint32_t phase;
    __device__ __forceinline__ uint32_t acquire(uint32_t ring) {
        mbar_wait(full + 8 * slot, phase);
        return ring + slot * kStageBytes;
    }
    __device__ __forceinline__ void release(int lane) {
        __syncwarp();
        if (lane == 0) mbar_arrive(empty + 8 * slot);
        skip();
    }
    __device__ __forceinline__ void skip() {
        if (++slot == kStages) { slot = 0; phase ^= 1; }
    }
};

__device__ __forceinline__ void gemv384(float (&acc)[3][4], uint32_t tile, const uint32_t (&off)[3], uint32_t bvec) {
    const uint4 b = lds128(bvec);
    uint32_t a[2][3][4];
#pragma unroll
    for (int ks = 0; ks < 2; ks++)
#pragma unroll
        for (int m = 0; m < 3; m++) ldsm4t(a[ks][m], tile + off[m] + ks * (16 * 384));
#pragma unroll
    for (int m = 0; m < 3; m++) mma(acc[m], a[0][m], b.x, b.y);
#pragma unroll
    for (int m = 0; m < 3; m++) mma(acc[m], a[1][m], b.z, b.w);
}

__device__ __forceinline__ void zero3(float (&acc)[3][4]) {
#pragma unroll
    for (int m = 0; m < 3; m++)
#pragma unroll
        for (int i = 0; i < 4; i++) acc[m][i] = 0.f;
}

__device__ __forceinline__ void first_loads(const CUtensorMap* wq, uint32_t sm, int h, int j, uint64_t pol) {
#pragma unroll
    for (int i = 0; i < kLdGate; i++) {
        const uint32_t bar = sm + kOffBar + 8 * i;
        mbar_init(bar, 1);
        asm volatile("fence.mbarrier_init.release.cluster;" ::: "memory");
        tma3(sm + i * kStageBytes, wq + (WQ32 || i == 2), 0, 3 * h, 160 * j + 64 * i, bar, pol);
        if (WQ32 && i < 2) tma3(sm + i * kStageBytes + kStageBytes / 2, wq + 1, 0, 3 * h, 160 * j + 64 * i + 32, bar, pol);
        mbar_expect_tx(bar, load_bytes(i));
    }
}

__device__ __forceinline__ void producer(const Maps& maps, uint32_t sm, int h, int j, uint64_t pol) {
    const uint32_t full = sm + kOffBar, empty = full + 8 * kStages;
    const int kvrow = h * kSk + j * (kTiles * 64);
    int landed = 0, need = kCtas * (units_through(kLdGate - 1) - kWindow - START_BOOST) - h * kStagger;
    int slot = kLdGate; uint32_t phase = 1;
    const int gate = kLdGate + GATE_TILE(h);
    const int fin = blockIdx.x - kFirstFinisher, loads = fin >= 0 ? kLoads : kLdDown;
#pragma unroll 1
    for (int i = kLdGate; i < loads; i++) {
        const uint32_t bar = full + 8 * slot, dst = sm + slot * kStageBytes;
        const CUtensorMap* tm; int c1, c2; uint32_t bytes;
        if (i < gate)          { tm = &maps.k;    c1 = 0;     c2 = kvrow + 64 * (i - kLdGate);    bytes = kStageBytes; }
        else if (i < gate + 2) { tm = &maps.gate + (i - gate); c1 = h; c2 = 160 * j;              bytes = 160 * 96; }
        else if (i < kLdV)     { tm = &maps.k;    c1 = 0;     c2 = kvrow + 64 * (i - kLdK);       bytes = kStageBytes; }
        else if (i < kLdWo)    { tm = &maps.v;    c1 = 0;     c2 = kvrow + 64 * (i - kLdV);       bytes = kStageBytes; }
        else if (i < kLdDown)  { tm = &maps.wo;   c1 = 5 * j; c2 = kDh * h + 64 * (i - kLdWo);    bytes = 64 * 320; }
        else                   { tm = &maps.down; c1 = fin;   c2 = 768 * (i - kLdDown);           bytes = kStageBytes; }
        need += bytes * kCtas / kUnit;
        if (i >= kLdDown) need = kCtas * (units_through(kLdDown - 1) - WINDOW_END) + (i == kLdDown ? DOWN0 : DOWN1);
        if (i == END_FROM) need += kCtas * (kWindow - WINDOW_END);
        if (i >= kLdWo - RAMP && i < kLdWo) need += (h - 16) * RAMP_STEP;
        if (i == kLdWo) need -= (h - 16) * WO_STEP;
        if (i == kLdWo + 2) need += (h - WO2_C) * WO2_FLAT;
        if (i == BOOST_UNTIL) need += kCtas * START_BOOST;
        if (i >= kStages) mbar_wait(empty + 8 * slot, phase);
        for (unsigned n = 0; landed < need; n++) {
            unsigned total;
            asm volatile("ld.relaxed.gpu.global.u32 %0, [%1];" : "=r"(total) : "l"(g_landed) : "memory");
            landed = (int)(total & (kLaunchUnits - 1));
            if (n > kSpinLimit) __trap();
        }
        mbar_expect_tx(bar, bytes);
        tma3(dst, tm, 0, c1, c2, bar, pol);
        if (i >= kLdDown) {
            tma3(dst + 8192, tm, 0, c1, c2 + 256, bar, pol);
            tma3(dst + 16384, tm, 0, c1, c2 + 512, bar, pol);
        }
        if (++slot == kStages) { slot = 0; phase ^= 1; }
    }
    if (blockIdx.x == kCtas - 1)
        asm volatile("red.relaxed.gpu.global.add.u32 [%0], %1;" :: "l"(g_landed), "r"(kPadUnits) : "memory");
    TR(true, 2);
}

__device__ __forceinline__ void monitor(uint32_t sm, int h) {
    const int gate = kLdGate + GATE_TILE(h);
    const uint32_t full = sm + kOffBar, empty = full + 8 * kStages;
    int slot = 0; uint32_t phase = 0;
    const int loads = blockIdx.x >= kFirstFinisher ? kLoads : kLdDown;
#pragma unroll 1
    for (int i = 0; i < loads; i++) {
        mbar_wait(full + 8 * slot, phase);
        const int k = i < kLdGate || i >= kLdV ? i : i == gate || i == gate + 1 ? kLdGate : kLdK;
        const int units = load_bytes(k) / kUnit;
        asm volatile("red.relaxed.gpu.global.add.u32 [%0], %1;" :: "l"(g_landed), "r"(units) : "memory");
        mbar_arrive(empty + 8 * slot);
        if (++slot == kStages) { slot = 0; phase ^= 1; }
    }
}

__device__ __forceinline__ void layer_norm(const __nv_bfloat16* __restrict__ x, uint8_t* smem, int j) {
    const int tid = threadIdx.x, lane = tid & 31;
    const uint4* x4 = reinterpret_cast<const uint4*>(x);
    uint4 xv[3];
    xv[0] = __ldg(x4 + lane);
    xv[1] = __ldg(x4 + 32 + lane);
    xv[2] = lane < 16 ? __ldg(x4 + 64 + lane) : make_uint4(0, 0, 0, 0);
    uint32_t xs = 0;
    if (tid < 80) xs = __ldg(reinterpret_cast<const uint32_t*>(x) + j * 80 + tid);

    for (int i = tid; i < (kOffRed - kOffXn) / 16; i += 128)
        *reinterpret_cast<uint4*>(smem + kOffXn + i * 16) = make_uint4(0, 0, 0, 0);

    float sum = 0.f;
#pragma unroll
    for (int i = 0; i < 3; i++) {
        const uint32_t u[4] = {xv[i].x, xv[i].y, xv[i].z, xv[i].w};
#pragma unroll
        for (int k = 0; k < 4; k++) sum += bf_lo(u[k]) + bf_hi(u[k]);
    }
#pragma unroll
    for (int s = 16; s > 0; s >>= 1) sum += __shfl_xor_sync(~0u, sum, s);
    const float mean = sum * (1.0f / kD);
    float sq = 0.f;
#pragma unroll
    for (int i = 0; i < 3; i++) {
        const uint32_t u[4] = {xv[i].x, xv[i].y, xv[i].z, xv[i].w};
        if (i < 2 || lane < 16) {
#pragma unroll
            for (int k = 0; k < 4; k++) {
                const float a = bf_lo(u[k]) - mean, b = bf_hi(u[k]) - mean;
                sq += a * a + b * b;
            }
        }
    }
#pragma unroll
    for (int s = 16; s > 0; s >>= 1) sq += __shfl_xor_sync(~0u, sq, s);
    const float mean_b = bf16r(mean);
    const float den = bf16r(__fsqrt_rn(bf16r(bf16r(sq * (1.0f / kD)) + 1e-5f)));
    bar_sync<kBarMain, 128>();
    if (tid < 80) {
        const int k = 2 * tid;
        const float a = __fdividef(bf16r(bf_lo(xs) - mean_b), den), b = __fdividef(bf16r(bf_hi(xs) - mean_b), den);
        const int off = (k >> 5) * 128 + ((k & 7) >> 1) * 16 + ((k >> 4) & 1) * 8 + ((k >> 3) & 1) * 4;
        *reinterpret_cast<uint32_t*>(smem + kOffXn + off) = pack_bf16(a, b);
    }
}

__device__ __forceinline__ void gate_up(Ring& ring, uint32_t sm) {
    const int lane = threadIdx.x & 31, w = threadIdx.x >> 5;
    const int quad = lane & 3, r = lane >> 2, mi = lane >> 3, lr = lane & 7;
    const uint32_t bsel = (r & 1) * 64 + quad * 16;
    const uint32_t off = ((mi >> 1) * 8 + lr) * 96 + (2 * w + (mi & 1)) * 16;
    uint32_t g0 = 0, g1 = 0;
#pragma unroll 1
    for (int g = 0; g < 2; g++) {
        const uint32_t tile = ring.acquire(sm);
        if (w < 3) {
            float c[4] = {0.f, 0.f, 0.f, 0.f};
#pragma unroll
            for (int kb = 0; kb < 5; kb++) {
                const uint4 b = lds128(sm + kOffXn + kb * 128 + bsel);
                uint32_t a0[4], a1[4];
                ldsm4t(a0, tile + off + kb * (32 * 96));
                ldsm4t(a1, tile + off + kb * (32 * 96) + 16 * 96);
                mma(c, a0, b.x, b.y);
                mma(c, a1, b.z, b.w);
            }
            if (g == 0) { g0 = tagged(c[0]); g1 = tagged(c[2]); }
            else put4(g_box + (blockIdx.x ^ quad) * kBoxWords + kBoxFfn + 96 * quad + 4 * (8 * w + r), g0, tagged(c[0]), g1, tagged(c[2]));
        }
        ring.release(lane);
    }
}

__device__ __forceinline__ float scores_softmax(Ring& ring, uint8_t* smem, uint32_t sm) {
    const int tid = threadIdx.x, lane = tid & 31, w = tid >> 5;
    const int quad = lane & 3, r = lane >> 2, mi = lane >> 3, lr = lane & 7;
    float* score = reinterpret_cast<float*>(smem + kOffScore);
    float* red = reinterpret_cast<float*>(smem + kOffRed);
    uint32_t qf[24];
#pragma unroll
    for (int kb = 0; kb < 6; kb++) {
        const uint4 b = lds128(sm + kOffQ + kb * 128 + quad * 16);
        qf[4 * kb] = b.x; qf[4 * kb + 1] = b.y; qf[4 * kb + 2] = b.z; qf[4 * kb + 3] = b.w;
    }
    const int row = 16 * w + (mi & 1) * 8 + lr;
    uint32_t offk[3];
#pragma unroll
    for (int seg = 0; seg < 3; seg++)
        offk[seg] = row * 384 + seg * 128 + (((mi >> 1) ^ ((3 * row + seg) & 7)) << 4);
    const float scale = 0.07216878364870323f;
    float mx = -INFINITY;
#pragma unroll 1
    for (int t = 0; t < kTiles; t++) {
        if (t == GATE_TILE(blockIdx.x >> 2)) {
            gate_up(ring, sm);
            TR(tid == 0, 5);
        }
        const uint32_t tile = ring.acquire(sm);
        float c0[4] = {0.f, 0.f, 0.f, 0.f}, c1[4] = {0.f, 0.f, 0.f, 0.f};
        uint32_t a[12][4];
#pragma unroll
        for (int ks = 0; ks < 12; ks++) ldsm4(a[ks], tile + (offk[ks >> 2] ^ ((ks & 3) << 5)));
#pragma unroll
        for (int ks = 0; ks < 12; ks += 2) {
            mma(c0, a[ks], qf[2 * ks], qf[2 * ks + 1]);
            mma(c1, a[ks + 1], qf[2 * ks + 2], qf[2 * ks + 3]);
        }
        ring.release(lane);
        const float s = bf16r(bf16r((quad & 1) ? c0[2] + c1[2] : c0[0] + c1[0]) * scale);
        mx = fmaxf(mx, s);
        if (quad < 2) score[t * 64 + 16 * w + quad * 8 + r] = s;
    }
#pragma unroll
    for (int s = 16; s > 0; s >>= 1) mx = fmaxf(mx, __shfl_xor_sync(~0u, mx, s));
    if (lane == 0) red[w] = mx;
    bar_sync<kBarMain, 128>();
    TR(tid == 0, 7);
    mx = fmaxf(fmaxf(red[0], red[1]), fmaxf(red[2], red[3]));

    float lsum = 0.f;
    const int blk = tid >> 2;
    uint32_t hi[4], lo[4];
#pragma unroll
    for (int i = 0; i < 4; i++) {
        const float2 s = *reinterpret_cast<const float2*>(score + blk * 32 + i * 8 + 2 * quad);
        const float e0 = __expf(s.x - mx), e1 = __expf(s.y - mx);
        lsum += e0 + e1;
        hi[i] = pack_bf16(e0, e1);
        lo[i] = pack_bf16(e0 - bf_lo(hi[i]), e1 - bf_hi(hi[i]));
    }
    *reinterpret_cast<uint4*>(smem + kOffP + blk * 128 + quad * 16) = make_uint4(hi[0], hi[1], hi[2], hi[3]);
    *reinterpret_cast<uint4*>(smem + kOffP + blk * 128 + 64 + quad * 16) = make_uint4(lo[0], lo[1], lo[2], lo[3]);
#pragma unroll
    for (int s = 16; s > 0; s >>= 1) lsum += __shfl_xor_sync(~0u, lsum, s);
    if (lane == 0) red[4 + w] = lsum;
    return mx;
}

__device__ __forceinline__ void consumer(const __nv_bfloat16* __restrict__ x, uint8_t* smem, uint32_t sm, int j) {
    const int tid = threadIdx.x, lane = tid & 31, w = tid >> 5;
    const int quad = lane & 3, r = lane >> 2, mi = lane >> 3, lr = lane & 7;
    const int cta = blockIdx.x;
    float* red = reinterpret_cast<float*>(smem + kOffRed);

    layer_norm(x, smem, j);
    bar_sync<kBarInit, 480>();
    TR(tid == 0, 3);

    Ring ring{sm + kOffBar, sm + kOffBar + 8 * kStages, 0, 0};
    const uint32_t bsel = (r & 1) * 64 + quad * 16;
    const int frow = (mi >> 1) * 8 + lr;
    uint32_t off384[3];
#pragma unroll
    for (int m = 0; m < 3; m++) {
        const int chunk = 2 * (3 * w + m) + (mi & 1), seg = chunk >> 3;
        off384[m] = frow * 384 + seg * 128 + (((chunk & 7) ^ ((3 * frow + seg) & 7)) << 4);
    }

#pragma unroll 1
    for (int pass = 0; pass < 2; pass++) {
        const int mt = 3 * w + quad, word = (pass && !ALIAS_O ? kBoxO : kBoxQ) + 16 * mt + 2 * r;
        uint32_t* send[3];
#pragma unroll
        for (int i = 0; i < 3; i++) {
            send[i] = g_box + (cta ^ (i + 1)) * kBoxWords + 192 * (i + 1) + word;
            pin(send[i]);
        }
        uint32_t* recv = g_box + cta * kBoxWords + 192 + word;
        uint32_t vec = sm + kOffQ + bvec_off(mt, r);
        pin(recv);
        pin(vec);

        float acc[3][4];
        zero3(acc);
        const int halves = pass ? 2 * kTiles : 5;
        uint32_t bv = sm + (pass ? kOffP : kOffXn) + bsel;
#pragma unroll 1
        for (int t = 0; t < halves; t += 2) {
            const uint32_t tile = ring.acquire(sm);
            gemv384(acc, tile, off384, bv);
            if (t + 1 < halves) gemv384(acc, tile + 32 * 384, off384, bv + 128);
            ring.release(lane);
            bv += 256;
        }
        TR(tid == 0, pass ? 9 : 4);
        float f = 1.f;
        if (pass) {
            bar_arrive<kBarGate, 448>();
            bar_sync<kBarScale, 160>();
            f = red[8];
        }

        const uint32_t a = tagged(f * pick3(quad, acc[0][0] + acc[0][1], acc[1][0] + acc[1][1], acc[2][0] + acc[2][1]));
        const uint32_t b = tagged(f * pick3(quad, acc[0][2] + acc[0][3], acc[1][2] + acc[1][3], acc[2][2] + acc[2][3]));
        if (quad < 3) {
#pragma unroll
            for (int i = 0; i < 3; i++) put2(send[i], a, b);
        }
        __syncwarp();
        uint64_t v[3];
        v[0] = v[1] = v[2] = 0;
        if (pass ? O_DELAY : Q_DELAY) __nanosleep(pass ? O_DELAY : Q_DELAY);
        if (O_SPIN) spin(O_SPIN);
        if (quad < 3) gather([&](int i) { return recv + 192 * i; }, v, 0x77777777u, pass ? O_SLEEP : Q_SLEEP);
        __syncwarp();
        const uint32_t s0 = pack_bf16((untagged(a) + untagged((uint32_t)v[0])) + (untagged((uint32_t)v[1]) + untagged((uint32_t)v[2])), 0.f);
        const uint32_t s1 = pack_bf16((untagged(b) + untagged((uint32_t)(v[0] >> 32))) +
                                      (untagged((uint32_t)(v[1] >> 32)) + untagged((uint32_t)(v[2] >> 32))), 0.f);
        asm volatile("{\n.reg .pred p;\nsetp.ne.u32 p, %3, 3;\n@p st.shared.u16 [%0], %1;\n@p st.shared.u16 [%0 + 4], %2;\n}"
                     :: "r"(vec), "h"((uint16_t)s0), "h"((uint16_t)s1), "r"(quad) : "memory");
        __syncwarp();
        if (pass && lane == 0) mbar_arrive(sm + kOffVecBar);
        if (pass) {
            TR(tid == 0, 10);
            break;
        }
        bar_sync<kBarMain, 128>();
        TR(tid == 0 && red[9] != 77.f, 6);
        const float mx = scores_softmax(ring, smem, sm);
        bar_sync<kBarMain, 128>();
        if (tid < 4) put2(g_box + (cta ^ tid) * kBoxWords + kBoxStat + 8 * tid, tagged(mx), tagged((red[4] + red[5]) + (red[6] + red[7])));
        if (w == 0) { __syncwarp(); bar_arrive<kBarStat, 160>(); }
        TR(tid == 0, 8);
    }
}

__device__ __forceinline__ void projector(const __nv_bfloat16* __restrict__ x, __nv_bfloat16* __restrict__ out, uint8_t* smem,
                                          uint32_t sm, int h, int j) {
    const int t = threadIdx.x - 192, lane = t & 31, w = t >> 5;
    const int quad = lane & 3, r = lane >> 2, mi = lane >> 3, lr = lane & 7;
    const int cta = blockIdx.x, fin = cta - kFirstFinisher;
    uint32_t* box = g_box + cta * kBoxWords;
    const uint32_t full = sm + kOffBar;
    const float xin = fin >= 0 ? __bfloat162float(x[16 * fin + (lane & 15) / 2 + 8 * (lane & 1)]) : 0.f;
    uint32_t* hid_dst = g_hid + (10 * j + t / 24) * kF + 48 * h + 2 * (t % 24);

    if (t < (ALIAS_O ? 144 : 288)) {
        const int i = (t % 144) / 48 + 1;
        put4(g_box + (cta ^ i) * kBoxWords + (t < 144 ? kBoxQ : kBoxO) + 192 * i + 4 * (t % 48), 0, 0, 0, 0);
    }
    if (t < 96) { if (!NO_CLEAR) put4(g_box + (cta ^ (t / 24)) * kBoxWords + kBoxFfn + 4 * t, 0, 0, 0, 0); }
    else if (t < 104) put4(g_box + (cta ^ ((t - 96) / 2)) * kBoxWords + kBoxStat + 4 * (t - 96), 0, 0, 0, 0);
    else if (t >= 280) put4(g_out + ((10 * j + (t - 280) / 4) * kH + h) * 16 + 4 * (t & 3), 0, 0, 0, 0);
    if (t < 240 && !NO_CLEAR) put2(hid_dst, 0, 0);
    __syncwarp();
    bar_sync<kBarInit, 480>();

    if (w < 3) {
        bar_sync<kBarStat, 160>();
        uint32_t s[4];
        gather([&](int i) { return box + kBoxFfn + 96 * i + t; }, s, ~0u, 200);
        const float sum = bf16r((untagged(s[0]) + untagged(s[1])) + (untagged(s[2]) + untagged(s[3])));
        const float up = __shfl_down_sync(~0u, sum, 1);
        if (!(lane & 1))
            reinterpret_cast<uint32_t*>(smem + kOffSend)[16 * w + r + 4 * (lane & 2)] = tagged(bf16r(bf16r(silu(sum)) * up));
    } else if (w == 9) {
        bar_sync<kBarStat, 160>();
        uint64_t st[1] = {0};
        if (lane < 4) gather([&](int) { return box + kBoxStat + 8 * lane; }, st, 15u, 200);
        __syncwarp();
        const float m = untagged((uint32_t)st[0]), l = untagged((uint32_t)(st[0] >> 32));
        float gm = fmaxf(m, __shfl_xor_sync(~0u, m, 1));
        gm = fmaxf(gm, __shfl_xor_sync(~0u, gm, 2));
        const float e = __expf(m - gm);
        float den = e * l;
        den += __shfl_xor_sync(~0u, den, 1);
        den += __shfl_xor_sync(~0u, den, 2);
        if (lane == 0) reinterpret_cast<float*>(smem + kOffRed)[8] = __fdividef(e, den);
        __syncwarp();
        bar_arrive<kBarScale, 160>();
    }
    __syncwarp();
    bar_sync<kBarProj, 320>();
    if (t < 240) {
        const uint2 v = *reinterpret_cast<const uint2*>(smem + kOffSend + 8 * (t % 24));
        put2(hid_dst, v.x, v.y);
    }
    __syncwarp();
    if (fin >= 0) {
        if (w < 8) {
            if (HID_DELAY) __nanosleep(HID_DELAY);
            uint64_t v[3];
            gather([&](int i) { return g_hid + fin * kF + 2 * (t + 256 * i); }, v, ~0u, 200);
#pragma unroll
            for (int i = 0; i < 3; i++) {
                const int pair = t + 256 * i;
                const int off = (pair >> 4) * 64 + (pair & 3) * 16 + ((pair >> 3) & 1) * 8 + ((pair >> 2) & 1) * 4;
                *reinterpret_cast<uint32_t*>(smem + kOffHid + off) = __byte_perm((uint32_t)v[i], (uint32_t)(v[i] >> 32), 0x7632);
            }
        }
        bar_sync<kBarProj, 320>();
    }

    const uint32_t lin = ((mi >> 1) * 8 + lr) * 320 + (2 * w + (mi & 1)) * 16;
    constexpr int kSlotWo = kLdWo % kStages, kSlotDown = kLdDown % kStages;
    static_assert(kLdWo / kStages == (kLoads - 1) / kStages, "the last loads share a phase");
    constexpr uint32_t parity = (kLdWo / kStages) & 1;
    uint32_t wo = sm + kSlotWo * kStageBytes + (lin ^ (((lin >> 7) & 3) << 4));
    uint32_t lead = lane < 4, bv = sm + kOffQ + lane * 16;
    uint32_t* dst = g_out + ((10 * j + w) * kH + h) * 16 + 2 * r;
    pin(wo); pin(lead); pin(bv); pin(dst);

#pragma unroll 1
    for (uint32_t pass = 0; pass < 2; pass++) {
        uint32_t writer = pass && quad == 0;
        pin(writer);
        if (pass) bar_sync<kBarGate, 448>();
        uint32_t a[3][4][4];
        auto fetch = [&](int k) {
#pragma unroll
            for (int i = 0; i < 4; i++) ldsm4t(a[k][i], wo + k * kStageBytes + i * (16 * 320));
        };
#pragma unroll
        for (int k = 0; k < 2; k++) {
            if (pass) mbar_wait(full + 8 * (kSlotWo + k), parity);
            fetch(k);
        }
        float c[4][4];
#pragma unroll
        for (int k = 0; k < 4; k++) c[k][0] = c[k][1] = c[k][2] = c[k][3] = 0.f;
        uint4 b[6];
#pragma unroll
        for (int k = 0; k < 6; k++) b[k] = make_uint4(0, 0, 0, 0);

        bool have_tile = false;
        for (unsigned n = 0; !mbar_test(sm + kOffVecBar, 0) && pass; n++) {
            if (!have_tile && mbar_test(full + 8 * (kSlotWo + 2), parity)) {
                fetch(2);
                have_tile = true;
                TR(t == 0, 15);
            }
            if (n > kSpinLimit) __trap();
        }
        TR(t == 0 && pass, 13);
#pragma unroll
        for (int k = 0; k < 6; k++) lds128_if(b[k], bv + 128 * k, lead);
#pragma unroll
        for (int k = 0; k < 2; k++) {
            mma(c[0], a[k][0], b[2 * k].x, b[2 * k].y);
            mma(c[1], a[k][1], b[2 * k].z, b[2 * k].w);
            mma(c[2], a[k][2], b[2 * k + 1].x, b[2 * k + 1].y);
            mma(c[3], a[k][3], b[2 * k + 1].z, b[2 * k + 1].w);
        }
        if (!have_tile) {
            for (unsigned n = 0; !mbar_test(full + 8 * (kSlotWo + 2), parity) && pass; n++) if (n > kSpinLimit) __trap();
            TR(t == 0 && pass, 15);
            fetch(2);
        }
        mma(c[0], a[2][0], b[4].x, b[4].y);
        mma(c[1], a[2][1], b[4].z, b[4].w);
        mma(c[2], a[2][2], b[5].x, b[5].y);
        mma(c[3], a[2][3], b[5].z, b[5].w);
        put2_if(dst, tagged((c[0][0] + c[1][0]) + (c[2][0] + c[3][0])), tagged((c[0][2] + c[1][2]) + (c[2][2] + c[3][2])), writer);
        TR(t == 0 && pass, 12);
        TR(t == 288 && pass, 11);
        if (fin < 0) continue;

        if (w < 8) {
            const uint32_t dl = ((mi >> 1) * 8 + lr) * 32 + (mi & 1) * 16;
            uint32_t tile = sm + kSlotDown * kStageBytes + w * (96 * 32) + (dl ^ (((dl >> 7) & 1) << 4));
            uint32_t part = sm + kOffPart + r * 32 + w * 4;
            pin(tile); pin(part);
#pragma unroll
            for (int k = 0; k < 6; k++) lds128_if(b[k], sm + kOffHid + (24 * (k / 3) + 3 * w + k % 3) * 64 + lane * 16, lead);
#pragma unroll
            for (int k = 0; k < 3; k++) c[k][0] = c[k][1] = c[k][2] = c[k][3] = 0.f;
#pragma unroll
            for (int k = 0; k < 2; k++) {
                for (unsigned n = 0; !mbar_test(full + 8 * (kSlotDown + k), parity) && pass; n++) if (n > kSpinLimit) __trap();
                TR(t == 0 && pass, 18 + k);
                uint32_t f[6][4];
#pragma unroll
                for (int i = 0; i < 6; i++) ldsm4t(f[i], tile + k * kStageBytes + i * 512);
#pragma unroll
                for (int i = 0; i < 3; i++) mma(c[i], f[2 * i], b[3 * k + i].x, b[3 * k + i].y);
#pragma unroll
                for (int i = 0; i < 3; i++) mma(c[i], f[2 * i + 1], b[3 * k + i].z, b[3 * k + i].w);
            }
            asm volatile("{\n.reg .pred p;\nsetp.eq.u32 p, %3, 0;\n@p st.shared.f32 [%0], %1;\n@p st.shared.f32 [%0 + 256], %2;\n}"
                         :: "r"(part), "f"(c[0][0] + c[1][0] + c[2][0]), "f"(c[0][2] + c[1][2] + c[2][2]), "r"(quad) : "memory");
            __syncwarp();
            if (lane == 0) mbar_arrive(sm + kOffPartBar);
        } else if (w == 9) {
            const int col = (lane & 15) / 2 + 8 * (lane & 1);
            uint32_t* src = g_out + fin * (kH * 16) + lane;
            uint32_t* used = (pass ? g_out + fin * (kH * 16) : g_sink) + 4 * lane;
            __nv_bfloat16* res = (pass ? out + 16 * fin : reinterpret_cast<__nv_bfloat16*>(g_sink)) + col;
            uint32_t part = sm + kOffPart + col * 32;
            pin(src); pin(used); pin(res); pin(part);
            auto gate = [&]() {
                const uint4 p0 = lds128(part), p1 = lds128(part + 16);
                const float d = ((__uint_as_float(p0.x) + __uint_as_float(p0.y)) + (__uint_as_float(p0.z) + __uint_as_float(p0.w))) +
                                ((__uint_as_float(p1.x) + __uint_as_float(p1.y)) + (__uint_as_float(p1.z) + __uint_as_float(p1.w)));
                return bf16r(silu(bf16r(d)));
            };
            uint32_t v[16];
#pragma unroll
            for (int i = 0; i < 16; i++) v[i] = pass ^ 1;
            float g = 0.f;
            bool have_g = false;
            const uint32_t start = clock_lo();
            for (unsigned n = 0;; n++) {
#pragma unroll
                for (int i = 0; i < 16; i++) peek(src + 32 * i, v[i]);
                if (!have_g && (mbar_test(sm + kOffPartBar, pass) || !pass)) {
                    g = gate();
                    have_g = pass;
                }
                uint32_t have = ~(uint32_t)((int)(clock_lo() - start) >> 31);
#pragma unroll
                for (int i = 0; i < 16; i++) have &= v[i];
                pin(have);
                if (__all_sync(~0u, have & 1)) break;
                if (n > kSpinLimit) __trap();
            }
            float sum[8];
#pragma unroll
            for (int i = 0; i < 8; i++) sum[i] = __uint_as_float(v[i]) + __uint_as_float(v[i + 8]);
            float s = ((sum[0] + sum[1]) + (sum[2] + sum[3])) + ((sum[4] + sum[5]) + (sum[6] + sum[7]));
            s = bf16r(s + __shfl_xor_sync(~0u, s, 16));
            TR(lane == 0 && pass, 16);
            if (!have_g) {
                for (unsigned n = 0; !mbar_test(sm + kOffPartBar, pass); n++) if (n > kSpinLimit) __trap();
                g = gate();
            }
            *res = __float2bfloat16_rn(xin + bf16r(s * g));
            TR(lane == 0 && pass, 17);
#pragma unroll
            for (int i = 0; i < 4; i++) put4(used + 128 * i, 0, 0, 0, 0);
        }
    }
}

__global__ void __launch_bounds__(kThreads, 1)
decode_block_kernel(const __grid_constant__ Maps maps, const __nv_bfloat16* __restrict__ x, __nv_bfloat16* __restrict__ out) {
    extern __shared__ __align__(1024) uint8_t smem[];
    const uint32_t sm = (uint32_t)__cvta_generic_to_shared(smem);
    const int w = threadIdx.x >> 5;
    const int h = blockIdx.x >> 2, j = blockIdx.x & 3;
    uint64_t pol;
    asm volatile("createpolicy.fractional.L2::evict_first.b64 %0, 1.0;" : "=l"(pol));
    asm volatile("{\n.reg .pred p;\n.reg .b32 t;\nmov.u32 t, %%tid.x;\nsetp.eq.u32 p, t, 0;\n"
                 "@p cp.async.bulk.prefetch.tensor.3d.L2.global.L2::cache_hint [%0, {0, %1, %2}], %3;\n}"
                 :: "l"(&maps.wq_tail), "r"(3 * h), "r"(160 * j + 32 * (PREFETCH2 - 1)), "l"(pol) : "memory");
    uint32_t sm0 = sm;
    const CUtensorMap* wq = &maps.wq;
    pin(sm0);
    pin(wq);
    if (threadIdx.x == 128) {
        first_loads(wq, sm0, h, j, pol);
        TR(true, 1);
#pragma unroll
        for (int i = 0; i < kStages; i++) {
            if (i >= kLdGate) mbar_init(sm + kOffBar + 8 * i, 1);
            mbar_init(sm + kOffBar + 8 * (kStages + i), 5);
        }
        mbar_init(sm + kOffVecBar, 4);
        mbar_init(sm + kOffPartBar, 8);
        asm volatile("fence.mbarrier_init.release.cluster;" ::: "memory");
    }
    __syncwarp();
    TR(threadIdx.x == 0, 0);
    if (w == 4) {
        bar_arrive<kBarMonitor, 64>();
        bar_arrive<kBarInit, 480>();
        if (threadIdx.x == 128) producer(maps, sm, h, j, pol);
    } else if (w == 5) {
        bar_sync<kBarMonitor, 64>();
        if (threadIdx.x == 160) monitor(sm, h);
    } else if (w < 4) {
        consumer(x, smem, sm, j);
    } else {
        projector(x, out, smem, sm, h, j);
    }
}

typedef CUresult (*EncodeFn)(CUtensorMap*, CUtensorMapDataType, cuuint32_t, void*, const cuuint64_t*, const cuuint64_t*,
                             const cuuint32_t*, const cuuint32_t*, CUtensorMapInterleave, CUtensorMapSwizzle,
                             CUtensorMapL2promotion, CUtensorMapFloatOOBfill);

void encode3(EncodeFn enc, CUtensorMap* tm, const void* p, uint64_t rows, uint64_t cols, uint32_t inner, uint32_t segs,
             uint32_t box_rows, CUtensorMapSwizzle sw, int promo = PROMO_ALL) {
    const cuuint64_t dims[3] = {inner, cols / inner, rows};
    const cuuint64_t strides[2] = {inner * 2ull, cols * 2ull};
    const cuuint32_t box[3] = {inner, segs, box_rows};
    const cuuint32_t es[3] = {1, 1, 1};
    enc(tm, CU_TENSOR_MAP_DATA_TYPE_BFLOAT16, 3, const_cast<void*>(p), dims, strides, box, es,
        CU_TENSOR_MAP_INTERLEAVE_NONE, sw, (CUtensorMapL2promotion)promo, CU_TENSOR_MAP_FLOAT_OOB_FILL_NONE);
}

}

extern "C" void kernel_launch(void* const* d_in, const int* in_sizes, int n_in, void* d_out, int out_size) {
    (void)in_sizes; (void)n_in; (void)out_size;
    static EncodeFn enc = nullptr;
    if (!enc) {
        void* fn = nullptr;
        cudaDriverEntryPointQueryResult qr;
        cudaGetDriverEntryPoint("cuTensorMapEncodeTiled", &fn, cudaEnableDefault, &qr);
        enc = (EncodeFn)fn;
        cudaFuncSetAttribute(decode_block_kernel, cudaFuncAttributeMaxDynamicSharedMemorySize, kSmemBytes);
    }
    Maps maps;
    encode3(enc, &maps.k, d_in[1], (uint64_t)kH * kSk, kDh, 64, 3, 64, CU_TENSOR_MAP_SWIZZLE_128B);
    encode3(enc, &maps.v, d_in[2], (uint64_t)kH * kSk, kDh, 64, 3, 64, CU_TENSOR_MAP_SWIZZLE_128B);
    encode3(enc, &maps.wq, d_in[3], kD, kH * kDh, 64, 3, 64, CU_TENSOR_MAP_SWIZZLE_128B);
    encode3(enc, &maps.wq_tail, d_in[3], kD, kH * kDh, 64, 3, 32, CU_TENSOR_MAP_SWIZZLE_128B);
    encode3(enc, &maps.wo, d_in[4], kH * kDh, kD, 32, 5, 64, CU_TENSOR_MAP_SWIZZLE_64B);
    encode3(enc, &maps.gate, d_in[6], kD, kF, 48, 1, 160, CU_TENSOR_MAP_SWIZZLE_NONE, PROMO_GATE);
    encode3(enc, &maps.up, d_in[7], kD, kF, 48, 1, 160, CU_TENSOR_MAP_SWIZZLE_NONE, PROMO_GATE);
    encode3(enc, &maps.down, d_in[8], kF, kD, 16, 1, 256, CU_TENSOR_MAP_SWIZZLE_32B, PROMO_DOWN);
    decode_block_kernel<<<kCtas, kThreads, kSmemBytes>>>(
        maps, (const __nv_bfloat16*)d_in[0], (__nv_bfloat16*)d_out);
}
```

```cpp
#include <cuda_runtime.h>
#include <cuda_bf16.h>
#include <cuda.h>
#include <stdint.h>

namespace {

constexpr int kH = 32, kSk = 4096, kDh = 192, kD = 640, kF = 1536;
constexpr int kCtas = 128, kThreads = 512;
constexpr int kFinishers = kD / 16, kFirstFinisher = kCtas - kFinishers;
constexpr int kStageBytes = 24576, kStages = 9;
constexpr int kTiles = 16;
constexpr int kLdGate = 3, kLdK = 5, kLdV = kLdK + kTiles, kLdWo = kLdV + kTiles;
constexpr int kLdDown = kLdWo + 3, kLoads = kLdDown + 2;

__host__ __device__ constexpr int load_bytes(int i) {
    return i == 2 ? kStageBytes / 2 : i >= kLdGate && i < kLdK ? 160 * 96 : i >= kLdWo && i < kLdDown ? 64 * 320 : kStageBytes;
}
__device__ __forceinline__ int gate_tile(int h) { return 2 * (h >> 2) + 1; }

constexpr int kUnit = 512, kWindow = 216, kWindowEnd = 128, kStagger = 192;
constexpr int kLdPaced = 8, kDepth = 3;
__host__ __device__ constexpr int units_through(int i) {
    int sum = 0;
    for (int k = 0; k <= i; k++) sum += load_bytes(k) / kUnit;
    return sum;
}
constexpr int kLaunchUnits = 1 << 18;
constexpr int kPadUnits = kLaunchUnits - kCtas * units_through(kLdDown - 1) - kFinishers * 2 * (kStageBytes / kUnit);
static_assert(kPadUnits >= 0, "padding");

constexpr int kOffScore = kStages * kStageBytes;
constexpr int kOffP = kOffScore + 4096;
constexpr int kOffXn = kOffP + 4096;
constexpr int kOffQ = kOffXn + 640;
constexpr int kOffSend = kOffQ + 768;
constexpr int kOffRed = kOffSend + 192;
constexpr int kOffBar = kOffRed + 48;
constexpr int kOffVecBar = kOffBar + 16 * kStages;
constexpr int kOffPartBar = kOffVecBar + 8;
constexpr int kSmemBytes = kOffPartBar + 8;
constexpr int kOffHid = kOffScore;
constexpr int kOffPart = kOffHid + 2 * kF;

constexpr int kBoxQ = -192, kBoxO = 384, kBoxFfn = 1152, kBoxStat = 1536, kBoxWords = 1568;
constexpr unsigned kSpinLimit = 1u << 24;

constexpr int kBarMain = 1, kBarInit = 2, kBarMonitor = 3, kBarStat = 4, kBarGate = 5, kBarScale = 6, kBarProj = 7;

struct Maps { CUtensorMap wq, wq_tail, gate, up, k, v, down, wo; };

__device__ __align__(128) uint32_t g_box[kCtas * kBoxWords];
__device__ __align__(128) uint32_t g_hid[kFinishers * kF];
__device__ __align__(128) uint32_t g_out[kFinishers * kH * 16];
__device__ __align__(128) uint32_t g_sink[kH * 16];
__device__ __align__(128) unsigned g_landed[32];


__device__ __forceinline__ void mbar_init(uint32_t bar, uint32_t cnt) {
    asm volatile("mbarrier.init.shared::cta.b64 [%0], %1;" :: "r"(bar), "r"(cnt) : "memory");
}
__device__ __forceinline__ void mbar_expect_tx(uint32_t bar, uint32_t bytes) {
    asm volatile("mbarrier.arrive.expect_tx.shared::cta.b64 _, [%0], %1;" :: "r"(bar), "r"(bytes) : "memory");
}
__device__ __forceinline__ void mbar_arrive(uint32_t bar) {
    asm volatile("mbarrier.arrive.shared::cta.b64 _, [%0];" :: "r"(bar) : "memory");
}
__device__ __forceinline__ bool mbar_try(uint32_t bar, uint32_t parity) {
    uint32_t ok;
    asm volatile("{\n.reg .pred p;\nmbarrier.try_wait.parity.shared::cta.b64 p, [%1], %2;\nselp.u32 %0, 1, 0, p;\n}"
                 : "=r"(ok) : "r"(bar), "r"(parity) : "memory");
    return ok;
}
__device__ __forceinline__ bool mbar_test(uint32_t bar, uint32_t parity) {
    uint32_t ok;
    asm volatile("{\n.reg .pred p;\nmbarrier.test_wait.parity.shared::cta.b64 p, [%1], %2;\nselp.u32 %0, 1, 0, p;\n}"
                 : "=r"(ok) : "r"(bar), "r"(parity) : "memory");
    return ok;
}
__device__ __forceinline__ void mbar_wait(uint32_t bar, uint32_t parity) {
    unsigned n = 0;
    while (!mbar_try(bar, parity)) { if (++n > kSpinLimit) __trap(); }
}
__device__ __forceinline__ void tma3(uint32_t dst, const CUtensorMap* tm, int c0, int c1, int c2, uint32_t bar, uint64_t pol) {
    asm volatile("cp.async.bulk.tensor.3d.shared::cluster.global.mbarrier::complete_tx::bytes.L2::cache_hint"
                 " [%0], [%1, {%3, %4, %5}], [%2], %6;"
                 :: "r"(dst), "l"(tm), "r"(bar), "r"(c0), "r"(c1), "r"(c2), "l"(pol) : "memory");
}
__device__ __forceinline__ void ldsm4(uint32_t (&a)[4], uint32_t addr) {
    asm volatile("ldmatrix.sync.aligned.m8n8.x4.shared.b16 {%0,%1,%2,%3}, [%4];"
                 : "=r"(a[0]), "=r"(a[1]), "=r"(a[2]), "=r"(a[3]) : "r"(addr) : "memory");
}
__device__ __forceinline__ void ldsm4t(uint32_t (&a)[4], uint32_t addr) {
    asm volatile("ldmatrix.sync.aligned.m8n8.x4.trans.shared.b16 {%0,%1,%2,%3}, [%4];"
                 : "=r"(a[0]), "=r"(a[1]), "=r"(a[2]), "=r"(a[3]) : "r"(addr) : "memory");
}
__device__ __forceinline__ void mma(float (&c)[4], const uint32_t (&a)[4], uint32_t b0, uint32_t b1) {
    asm("mma.sync.aligned.m16n8k16.row.col.f32.bf16.bf16.f32 {%0,%1,%2,%3}, {%4,%5,%6,%7}, {%8,%9}, {%0,%1,%2,%3};"
                 : "+f"(c[0]), "+f"(c[1]), "+f"(c[2]), "+f"(c[3])
                 : "r"(a[0]), "r"(a[1]), "r"(a[2]), "r"(a[3]), "r"(b0), "r"(b1));
}
__device__ __forceinline__ uint4 lds128(uint32_t addr) {
    uint4 v;
    asm volatile("ld.shared.v4.u32 {%0,%1,%2,%3}, [%4];" : "=r"(v.x), "=r"(v.y), "=r"(v.z), "=r"(v.w) : "r"(addr) : "memory");
    return v;
}
__device__ __forceinline__ void lds128_if(uint4& v, uint32_t addr, uint32_t p) {
    asm volatile("{\n.reg .pred p;\nsetp.ne.u32 p, %5, 0;\n@p ld.shared.v4.u32 {%0,%1,%2,%3}, [%4];\n}"
                 : "+r"(v.x), "+r"(v.y), "+r"(v.z), "+r"(v.w) : "r"(addr), "r"(p) : "memory");
}
__device__ __forceinline__ void pin(uint32_t& v) { asm volatile("" : "+r"(v)); }
__device__ __forceinline__ void pin(float& v) { asm volatile("" : "+f"(v)); }
template <typename T> __device__ __forceinline__ void pin(T*& p) { asm volatile("" : "+l"(p)); }
template <int kId, int kCount> __device__ __forceinline__ void bar_sync() {
    asm volatile("bar.sync %0, %1;" :: "n"(kId), "n"(kCount) : "memory");
}
template <int kId, int kCount> __device__ __forceinline__ void bar_arrive() {
    asm volatile("bar.arrive %0, %1;" :: "n"(kId), "n"(kCount) : "memory");
}

__device__ __forceinline__ uint32_t tagged(float v) { return __float_as_uint(v) | 1u; }
__device__ __forceinline__ float untagged(uint32_t w) { return __uint_as_float(w & ~1u); }
__device__ __forceinline__ void put2(uint32_t* p, uint32_t a, uint32_t b) {
    asm volatile("st.relaxed.gpu.global.b64 [%0], %1;" :: "l"(p), "l"(((uint64_t)b << 32) | a) : "memory");
}
__device__ __forceinline__ void put2_if(uint32_t* p, uint32_t a, uint32_t b, uint32_t pred) {
    asm volatile("{\n.reg .pred p;\nsetp.ne.u32 p, %2, 0;\n@p st.relaxed.gpu.global.b64 [%0], %1;\n}"
                 :: "l"(p), "l"(((uint64_t)b << 32) | a), "r"(pred) : "memory");
}
__device__ __forceinline__ void put4(uint32_t* p, uint32_t a, uint32_t b, uint32_t c, uint32_t d) {
    asm volatile("st.relaxed.gpu.global.v4.b32 [%0], {%1, %2, %3, %4};" :: "l"(p), "r"(a), "r"(b), "r"(c), "r"(d) : "memory");
}
__device__ __forceinline__ void take(uint32_t* p, uint32_t& w) {
    asm volatile("atom.relaxed.gpu.global.exch.b32 %0, [%1], 0;" : "=r"(w) : "l"(p) : "memory");
}
__device__ __forceinline__ void take(uint32_t* p, uint64_t& w) {
    asm volatile("atom.relaxed.gpu.global.exch.b64 %0, [%1], 0;" : "=l"(w) : "l"(p) : "memory");
}
template <typename Word, int kN, typename Addr>
__device__ __forceinline__ void gather(Addr addr, Word (&w)[kN], unsigned mask, unsigned sleep_ns) {
#pragma unroll
    for (int i = 0; i < kN; i++) w[i] = 0;
    for (unsigned n = 0;; n++) {
        Word t[kN];
#pragma unroll
        for (int i = 0; i < kN; i++) take(addr(i), t[i]);
        uint32_t have = ~0u;
#pragma unroll
        for (int i = 0; i < kN; i++) {
            w[i] |= t[i];
            have &= (uint32_t)w[i];
        }
        pin(have);
        if (__all_sync(mask, have & 1)) break;
        if (n > kSpinLimit) __trap();
        if (sleep_ns) __nanosleep(sleep_ns);
    }
}
__device__ __forceinline__ void peek(const uint32_t* p, uint32_t& w) {
    asm volatile("{\n.reg .pred p;\n.reg .b32 t;\n"
                 "and.b32 t, %0, 1;\nsetp.eq.u32 p, t, 0;\n"
                 "@p ld.relaxed.gpu.global.b32 %0, [%1];\n}"
                 : "+r"(w) : "l"(p) : "memory");
}
__device__ __forceinline__ uint32_t clock_lo() {
    uint32_t c;
    asm volatile("mov.u32 %0, %%clock;" : "=r"(c) :: "memory");
    return c;
}
__device__ __forceinline__ void spin(uint32_t cycles) {
    const uint32_t start = clock_lo();
    while (clock_lo() - start < cycles) {}
}

__device__ __forceinline__ float bf16r(float v) { return __bfloat162float(__float2bfloat16_rn(v)); }
__device__ __forceinline__ float bf_lo(uint32_t u) { return __uint_as_float(u << 16); }
__device__ __forceinline__ float bf_hi(uint32_t u) { return __uint_as_float(u & 0xffff0000u); }
__device__ __forceinline__ uint32_t pack_bf16(float lo, float hi) {
    __nv_bfloat162 t = __floats2bfloat162_rn(lo, hi);
    return *reinterpret_cast<uint32_t*>(&t);
}
__device__ __forceinline__ float silu(float v) { return __fdividef(v, 1.0f + __expf(-v)); }
__device__ __forceinline__ float pick3(int s, float a, float b, float c) { return s == 0 ? a : (s == 1 ? b : c); }

__device__ __forceinline__ int bvec_off(int mt, int r) {
    return (mt >> 1) * 128 + (r >> 1) * 16 + (mt & 1) * 8 + (r & 1) * 2;
}

struct Ring {
    uint32_t full, empty;
    int slot; uint32_t phase;
    __device__ __forceinline__ uint32_t acquire(uint32_t ring) {
        mbar_wait(full + 8 * slot, phase);
        return ring + slot * kStageBytes;
    }
    __device__ __forceinline__ void release(int lane) {
        __syncwarp();
        if (lane == 0) mbar_arrive(empty + 8 * slot);
        skip();
    }
    __device__ __forceinline__ void skip() {
        if (++slot == kStages) { slot = 0; phase ^= 1; }
    }
};

__device__ __forceinline__ void gemv384(float (&acc)[3][4], uint32_t tile, const uint32_t (&off)[3], uint32_t bvec) {
    const uint4 b = lds128(bvec);
    uint32_t a[2][3][4];
#pragma unroll
    for (int ks = 0; ks < 2; ks++)
#pragma unroll
        for (int m = 0; m < 3; m++) ldsm4t(a[ks][m], tile + off[m] + ks * (16 * 384));
#pragma unroll
    for (int m = 0; m < 3; m++) mma(acc[m], a[0][m], b.x, b.y);
#pragma unroll
    for (int m = 0; m < 3; m++) mma(acc[m], a[1][m], b.z, b.w);
}

__device__ __forceinline__ void zero3(float (&acc)[3][4]) {
#pragma unroll
    for (int m = 0; m < 3; m++)
#pragma unroll
        for (int i = 0; i < 4; i++) acc[m][i] = 0.f;
}

__device__ __forceinline__ void first_loads(const CUtensorMap* wq, uint32_t sm, int h, int j, uint64_t pol) {
#pragma unroll
    for (int i = 0; i < kLdGate; i++) {
        const uint32_t bar = sm + kOffBar + 8 * i;
        mbar_init(bar, 1);
        asm volatile("fence.mbarrier_init.release.cluster;" ::: "memory");
        tma3(sm + i * kStageBytes, wq + (i == 2), 0, 3 * h, 160 * j + 64 * i, bar, pol);
        mbar_expect_tx(bar, load_bytes(i));
    }
}

__device__ __forceinline__ void producer(const Maps& maps, uint32_t sm, int h, int j, uint64_t pol) {
    const uint32_t full = sm + kOffBar, empty = full + 8 * kStages;
    const int kvrow = h * kSk + j * (kTiles * 64);
    int landed = 0, need = kCtas * (units_through(kLdGate - 1) - kWindow) - h * kStagger;
    int slot = kLdGate; uint32_t phase = 1;
    const int gate = kLdGate + gate_tile(h);
    const int fin = blockIdx.x - kFirstFinisher, loads = fin >= 0 ? kLoads : kLdDown;
#pragma unroll 1
    for (int i = kLdGate; i < loads; i++) {
        const uint32_t bar = full + 8 * slot, dst = sm + slot * kStageBytes;
        const CUtensorMap* tm; int c1, c2; uint32_t bytes;
        if (i < gate)          { tm = &maps.k;    c1 = 0;     c2 = kvrow + 64 * (i - kLdGate);    bytes = kStageBytes; }
        else if (i < gate + 2) { tm = &maps.gate + (i - gate); c1 = h; c2 = 160 * j;              bytes = 160 * 96; }
        else if (i < kLdV)     { tm = &maps.k;    c1 = 0;     c2 = kvrow + 64 * (i - kLdK);       bytes = kStageBytes; }
        else if (i < kLdWo)    { tm = &maps.v;    c1 = 0;     c2 = kvrow + 64 * (i - kLdV);       bytes = kStageBytes; }
        else if (i < kLdDown)  { tm = &maps.wo;   c1 = 5 * j; c2 = kDh * h + 64 * (i - kLdWo);    bytes = 64 * 320; }
        else                   { tm = &maps.down; c1 = fin;   c2 = 768 * (i - kLdDown);           bytes = kStageBytes; }
        need += bytes * kCtas / kUnit;
        if (i >= kLdDown) need = kCtas * (units_through(kLdDown - 1) - kWindowEnd);
        if (i == kLdWo) need += kCtas * (kWindow - kWindowEnd);
        if (i == kLdDown - 1) need += (h - kH / 2) * kStagger;
        if (i >= kStages) mbar_wait(empty + 8 * slot, phase);
        if (i < kLdPaced) mbar_wait(full + 8 * (i - kDepth), 0);
        for (unsigned n = 0; landed < need && i >= kLdPaced; n++) {
            unsigned total;
            asm volatile("ld.relaxed.gpu.global.u32 %0, [%1];" : "=r"(total) : "l"(g_landed) : "memory");
            landed = (int)(total & (kLaunchUnits - 1));
            if (n > kSpinLimit) __trap();
        }
        mbar_expect_tx(bar, bytes);
        tma3(dst, tm, 0, c1, c2, bar, pol);
        if (i >= kLdDown) {
            tma3(dst + 8192, tm, 0, c1, c2 + 256, bar, pol);
            tma3(dst + 16384, tm, 0, c1, c2 + 512, bar, pol);
        }
        if (++slot == kStages) { slot = 0; phase ^= 1; }
    }
    if (blockIdx.x == kCtas - 1)
        asm volatile("red.relaxed.gpu.global.add.u32 [%0], %1;" :: "l"(g_landed), "r"(kPadUnits) : "memory");
}

__device__ __forceinline__ void monitor(uint32_t sm, int h) {
    const int gate = kLdGate + gate_tile(h);
    const uint32_t full = sm + kOffBar, empty = full + 8 * kStages;
    int slot = 0; uint32_t phase = 0;
    const int loads = blockIdx.x >= kFirstFinisher ? kLoads : kLdDown;
#pragma unroll 1
    for (int i = 0; i < loads; i++) {
        mbar_wait(full + 8 * slot, phase);
        const int k = i < kLdGate || i >= kLdV ? i : i == gate || i == gate + 1 ? kLdGate : kLdK;
        const int units = load_bytes(k) / kUnit;
        asm volatile("red.relaxed.gpu.global.add.u32 [%0], %1;" :: "l"(g_landed), "r"(units) : "memory");
        mbar_arrive(empty + 8 * slot);
        if (++slot == kStages) { slot = 0; phase ^= 1; }
    }
}

__device__ __forceinline__ void layer_norm(const __nv_bfloat16* __restrict__ x, uint8_t* smem, int j) {
    const int tid = threadIdx.x, lane = tid & 31;
    const uint4* x4 = reinterpret_cast<const uint4*>(x);
    uint4 xv[3];
    xv[0] = __ldg(x4 + lane);
    xv[1] = __ldg(x4 + 32 + lane);
    xv[2] = lane < 16 ? __ldg(x4 + 64 + lane) : make_uint4(0, 0, 0, 0);
    uint32_t xs = 0;
    if (tid < 80) xs = __ldg(reinterpret_cast<const uint32_t*>(x) + j * 80 + tid);

    for (int i = tid; i < (kOffRed - kOffXn) / 16; i += 128)
        *reinterpret_cast<uint4*>(smem + kOffXn + i * 16) = make_uint4(0, 0, 0, 0);

    float sum = 0.f;
#pragma unroll
    for (int i = 0; i < 3; i++) {
        const uint32_t u[4] = {xv[i].x, xv[i].y, xv[i].z, xv[i].w};
#pragma unroll
        for (int k = 0; k < 4; k++) sum += bf_lo(u[k]) + bf_hi(u[k]);
    }
#pragma unroll
    for (int s = 16; s > 0; s >>= 1) sum += __shfl_xor_sync(~0u, sum, s);
    const float mean = sum * (1.0f / kD);
    float sq = 0.f;
#pragma unroll
    for (int i = 0; i < 3; i++) {
        const uint32_t u[4] = {xv[i].x, xv[i].y, xv[i].z, xv[i].w};
        if (i < 2 || lane < 16) {
#pragma unroll
            for (int k = 0; k < 4; k++) {
                const float a = bf_lo(u[k]) - mean, b = bf_hi(u[k]) - mean;
                sq += a * a + b * b;
            }
        }
    }
#pragma unroll
    for (int s = 16; s > 0; s >>= 1) sq += __shfl_xor_sync(~0u, sq, s);
    const float mean_b = bf16r(mean);
    const float den = bf16r(__fsqrt_rn(bf16r(bf16r(sq * (1.0f / kD)) + 1e-5f)));
    bar_sync<kBarMain, 128>();
    if (tid < 80) {
        const int k = 2 * tid;
        const float a = __fdividef(bf16r(bf_lo(xs) - mean_b), den), b = __fdividef(bf16r(bf_hi(xs) - mean_b), den);
        const int off = (k >> 5) * 128 + ((k & 7) >> 1) * 16 + ((k >> 4) & 1) * 8 + ((k >> 3) & 1) * 4;
        *reinterpret_cast<uint32_t*>(smem + kOffXn + off) = pack_bf16(a, b);
    }
}

__device__ __forceinline__ void gate_up(Ring& ring, uint32_t sm) {
    const int lane = threadIdx.x & 31, w = threadIdx.x >> 5;
    const int quad = lane & 3, r = lane >> 2, mi = lane >> 3, lr = lane & 7;
    const uint32_t bsel = (r & 1) * 64 + quad * 16;
    const uint32_t off = ((mi >> 1) * 8 + lr) * 96 + (2 * w + (mi & 1)) * 16;
    uint32_t g0 = 0, g1 = 0;
#pragma unroll 1
    for (int g = 0; g < 2; g++) {
        const uint32_t tile = ring.acquire(sm);
        if (w < 3) {
            float c[4] = {0.f, 0.f, 0.f, 0.f};
#pragma unroll
            for (int kb = 0; kb < 5; kb++) {
                const uint4 b = lds128(sm + kOffXn + kb * 128 + bsel);
                uint32_t a0[4], a1[4];
                ldsm4t(a0, tile + off + kb * (32 * 96));
                ldsm4t(a1, tile + off + kb * (32 * 96) + 16 * 96);
                mma(c, a0, b.x, b.y);
                mma(c, a1, b.z, b.w);
            }
            if (g == 0) { g0 = tagged(c[0]); g1 = tagged(c[2]); }
            else put4(g_box + (blockIdx.x ^ quad) * kBoxWords + kBoxFfn + 96 * quad + 4 * (8 * w + r), g0, tagged(c[0]), g1, tagged(c[2]));
        }
        ring.release(lane);
    }
}

__device__ __forceinline__ float scores_softmax(Ring& ring, uint8_t* smem, uint32_t sm) {
    const int tid = threadIdx.x, lane = tid & 31, w = tid >> 5;
    const int quad = lane & 3, r = lane >> 2, mi = lane >> 3, lr = lane & 7;
    float* score = reinterpret_cast<float*>(smem + kOffScore);
    float* red = reinterpret_cast<float*>(smem + kOffRed);
    uint32_t qf[24];
#pragma unroll
    for (int kb = 0; kb < 6; kb++) {
        const uint4 b = lds128(sm + kOffQ + kb * 128 + quad * 16);
        qf[4 * kb] = b.x; qf[4 * kb + 1] = b.y; qf[4 * kb + 2] = b.z; qf[4 * kb + 3] = b.w;
    }
    const int row = 16 * w + (mi & 1) * 8 + lr;
    uint32_t offk[3];
#pragma unroll
    for (int seg = 0; seg < 3; seg++)
        offk[seg] = row * 384 + seg * 128 + (((mi >> 1) ^ ((3 * row + seg) & 7)) << 4);
    const float scale = 0.07216878364870323f;
    float mx = -INFINITY;
#pragma unroll 1
    for (int t = 0; t < kTiles; t++) {
        if (t == gate_tile(blockIdx.x >> 2)) gate_up(ring, sm);
        const uint32_t tile = ring.acquire(sm);
        float c0[4] = {0.f, 0.f, 0.f, 0.f}, c1[4] = {0.f, 0.f, 0.f, 0.f};
        uint32_t a[12][4];
#pragma unroll
        for (int ks = 0; ks < 12; ks++) ldsm4(a[ks], tile + (offk[ks >> 2] ^ ((ks & 3) << 5)));
#pragma unroll
        for (int ks = 0; ks < 12; ks += 2) {
            mma(c0, a[ks], qf[2 * ks], qf[2 * ks + 1]);
            mma(c1, a[ks + 1], qf[2 * ks + 2], qf[2 * ks + 3]);
        }
        ring.release(lane);
        const float s = bf16r(bf16r((quad & 1) ? c0[2] + c1[2] : c0[0] + c1[0]) * scale);
        mx = fmaxf(mx, s);
        if (quad < 2) score[t * 64 + 16 * w + quad * 8 + r] = s;
    }
#pragma unroll
    for (int s = 16; s > 0; s >>= 1) mx = fmaxf(mx, __shfl_xor_sync(~0u, mx, s));
    if (lane == 0) red[w] = mx;
    bar_sync<kBarMain, 128>();
    mx = fmaxf(fmaxf(red[0], red[1]), fmaxf(red[2], red[3]));

    float lsum = 0.f;
    const int blk = tid >> 2;
    uint32_t hi[4], lo[4];
#pragma unroll
    for (int i = 0; i < 4; i++) {
        const float2 s = *reinterpret_cast<const float2*>(score + blk * 32 + i * 8 + 2 * quad);
        const float e0 = __expf(s.x - mx), e1 = __expf(s.y - mx);
        lsum += e0 + e1;
        hi[i] = pack_bf16(e0, e1);
        lo[i] = pack_bf16(e0 - bf_lo(hi[i]), e1 - bf_hi(hi[i]));
    }
    *reinterpret_cast<uint4*>(smem + kOffP + blk * 128 + quad * 16) = make_uint4(hi[0], hi[1], hi[2], hi[3]);
    *reinterpret_cast<uint4*>(smem + kOffP + blk * 128 + 64 + quad * 16) = make_uint4(lo[0], lo[1], lo[2], lo[3]);
#pragma unroll
    for (int s = 16; s > 0; s >>= 1) lsum += __shfl_xor_sync(~0u, lsum, s);
    if (lane == 0) red[4 + w] = lsum;
    return mx;
}

__device__ __forceinline__ void consumer(const __nv_bfloat16* __restrict__ x, uint8_t* smem, uint32_t sm, int j) {
    const int tid = threadIdx.x, lane = tid & 31, w = tid >> 5;
    const int quad = lane & 3, r = lane >> 2, mi = lane >> 3, lr = lane & 7;
    const int cta = blockIdx.x;
    float* red = reinterpret_cast<float*>(smem + kOffRed);

    layer_norm(x, smem, j);
    bar_sync<kBarInit, 480>();

    Ring ring{sm + kOffBar, sm + kOffBar + 8 * kStages, 0, 0};
    const uint32_t bsel = (r & 1) * 64 + quad * 16;
    const int frow = (mi >> 1) * 8 + lr;
    uint32_t off384[3];
#pragma unroll
    for (int m = 0; m < 3; m++) {
        const int chunk = 2 * (3 * w + m) + (mi & 1), seg = chunk >> 3;
        off384[m] = frow * 384 + seg * 128 + (((chunk & 7) ^ ((3 * frow + seg) & 7)) << 4);
    }

#pragma unroll 1
    for (int pass = 0; pass < 2; pass++) {
        const int mt = 3 * w + quad, word = (pass ? kBoxO : kBoxQ) + 16 * mt + 2 * r;
        uint32_t* send[3];
#pragma unroll
        for (int i = 0; i < 3; i++) {
            send[i] = g_box + (cta ^ (i + 1)) * kBoxWords + 192 * (i + 1) + word;
            pin(send[i]);
        }
        uint32_t* recv = g_box + cta * kBoxWords + 192 + word;
        uint32_t vec = sm + kOffQ + bvec_off(mt, r);
        pin(recv);
        pin(vec);

        float acc[3][4];
        zero3(acc);
        const int halves = pass ? 2 * kTiles : 5;
        uint32_t bv = sm + (pass ? kOffP : kOffXn) + bsel;
#pragma unroll 1
        for (int t = 0; t < halves; t += 2) {
            const uint32_t tile = ring.acquire(sm);
            gemv384(acc, tile, off384, bv);
            if (t + 1 < halves) gemv384(acc, tile + 32 * 384, off384, bv + 128);
            ring.release(lane);
            bv += 256;
        }
        float f = 1.f;
        if (pass) {
            bar_arrive<kBarGate, 448>();
            bar_sync<kBarScale, 160>();
            f = red[8];
        }

        const uint32_t a = tagged(f * pick3(quad, acc[0][0] + acc[0][1], acc[1][0] + acc[1][1], acc[2][0] + acc[2][1]));
        const uint32_t b = tagged(f * pick3(quad, acc[0][2] + acc[0][3], acc[1][2] + acc[1][3], acc[2][2] + acc[2][3]));
        if (quad < 3) {
#pragma unroll
            for (int i = 0; i < 3; i++) put2(send[i], a, b);
        }
        __syncwarp();
        uint64_t v[3];
        v[0] = v[1] = v[2] = 0;
        if (!pass) __nanosleep(600);
        spin(1000);
        if (quad < 3) gather([&](int i) { return recv + 192 * i; }, v, 0x77777777u, pass ? 0 : 500);
        __syncwarp();
        const uint32_t s0 = pack_bf16((untagged(a) + untagged((uint32_t)v[0])) + (untagged((uint32_t)v[1]) + untagged((uint32_t)v[2])), 0.f);
        const uint32_t s1 = pack_bf16((untagged(b) + untagged((uint32_t)(v[0] >> 32))) +
                                      (untagged((uint32_t)(v[1] >> 32)) + untagged((uint32_t)(v[2] >> 32))), 0.f);
        asm volatile("{\n.reg .pred p;\nsetp.ne.u32 p, %3, 3;\n@p st.shared.u16 [%0], %1;\n@p st.shared.u16 [%0 + 4], %2;\n}"
                     :: "r"(vec), "h"((uint16_t)s0), "h"((uint16_t)s1), "r"(quad) : "memory");
        __syncwarp();
        if (pass && lane == 0) mbar_arrive(sm + kOffVecBar);
        if (pass) break;
        bar_sync<kBarMain, 128>();
        const float mx = scores_softmax(ring, smem, sm);
        bar_sync<kBarMain, 128>();
        if (tid < 4) put2(g_box + (cta ^ tid) * kBoxWords + kBoxStat + 8 * tid, tagged(mx), tagged((red[4] + red[5]) + (red[6] + red[7])));
        if (w == 0) { __syncwarp(); bar_arrive<kBarStat, 160>(); }
    }
}

__device__ __forceinline__ void projector(const __nv_bfloat16* __restrict__ x, __nv_bfloat16* __restrict__ out, uint8_t* smem,
                                          uint32_t sm, int h, int j) {
    const int t = threadIdx.x - 192, lane = t & 31, w = t >> 5;
    const int quad = lane & 3, r = lane >> 2, mi = lane >> 3, lr = lane & 7;
    const int cta = blockIdx.x, fin = cta - kFirstFinisher;
    uint32_t* box = g_box + cta * kBoxWords;
    const uint32_t full = sm + kOffBar;
    const float xin = fin >= 0 ? __bfloat162float(x[16 * fin + (lane & 15) / 2 + 8 * (lane & 1)]) : 0.f;
    uint32_t* hid_dst = g_hid + (10 * j + t / 24) * kF + 48 * h + 2 * (t % 24);

    if (t < 288) {
        const int i = (t % 144) / 48 + 1;
        put4(g_box + (cta ^ i) * kBoxWords + (t < 144 ? kBoxQ : kBoxO) + 192 * i + 4 * (t % 48), 0, 0, 0, 0);
    }
    if (t < 96) put4(g_box + (cta ^ (t / 24)) * kBoxWords + kBoxFfn + 4 * t, 0, 0, 0, 0);
    else if (t < 104) put4(g_box + (cta ^ ((t - 96) / 2)) * kBoxWords + kBoxStat + 4 * (t - 96), 0, 0, 0, 0);
    else if (t >= 280) put4(g_out + ((10 * j + (t - 280) / 4) * kH + h) * 16 + 4 * (t & 3), 0, 0, 0, 0);
    if (t < 240) put2(hid_dst, 0, 0);
    __syncwarp();
    bar_sync<kBarInit, 480>();

    if (w < 3) {
        bar_sync<kBarStat, 160>();
        uint32_t s[4];
        gather([&](int i) { return box + kBoxFfn + 96 * i + t; }, s, ~0u, 200);
        const float sum = bf16r((untagged(s[0]) + untagged(s[1])) + (untagged(s[2]) + untagged(s[3])));
        const float up = __shfl_down_sync(~0u, sum, 1);
        if (!(lane & 1))
            reinterpret_cast<uint32_t*>(smem + kOffSend)[16 * w + r + 4 * (lane & 2)] = tagged(bf16r(bf16r(silu(sum)) * up));
    } else if (w == 9) {
        bar_sync<kBarStat, 160>();
        uint64_t st[1] = {0};
        if (lane < 4) gather([&](int) { return box + kBoxStat + 8 * lane; }, st, 15u, 200);
        __syncwarp();
        const float m = untagged((uint32_t)st[0]), l = untagged((uint32_t)(st[0] >> 32));
        float gm = fmaxf(m, __shfl_xor_sync(~0u, m, 1));
        gm = fmaxf(gm, __shfl_xor_sync(~0u, gm, 2));
        const float e = __expf(m - gm);
        float den = e * l;
        den += __shfl_xor_sync(~0u, den, 1);
        den += __shfl_xor_sync(~0u, den, 2);
        if (lane == 0) reinterpret_cast<float*>(smem + kOffRed)[8] = __fdividef(e, den);
        __syncwarp();
        bar_arrive<kBarScale, 160>();
    }
    __syncwarp();
    bar_sync<kBarProj, 320>();
    if (t < 240) {
        const uint2 v = *reinterpret_cast<const uint2*>(smem + kOffSend + 8 * (t % 24));
        put2(hid_dst, v.x, v.y);
    }
    __syncwarp();
    if (fin >= 0) {
        if (w < 8) {
            __nanosleep(4000);
            uint64_t v[3];
            gather([&](int i) { return g_hid + fin * kF + 2 * (t + 256 * i); }, v, ~0u, 200);
    #pragma unroll
            for (int i = 0; i < 3; i++) {
                const int pair = t + 256 * i;
                const int off = (pair >> 4) * 64 + (pair & 3) * 16 + ((pair >> 3) & 1) * 8 + ((pair >> 2) & 1) * 4;
                *reinterpret_cast<uint32_t*>(smem + kOffHid + off) = __byte_perm((uint32_t)v[i], (uint32_t)(v[i] >> 32), 0x7632);
            }
        }
        bar_sync<kBarProj, 320>();
    }

    const uint32_t lin = ((mi >> 1) * 8 + lr) * 320 + (2 * w + (mi & 1)) * 16;
    constexpr int kSlotWo = kLdWo % kStages, kSlotDown = kLdDown % kStages;
    static_assert(kLdWo / kStages == (kLoads - 1) / kStages, "the last loads share a phase");
    constexpr uint32_t parity = (kLdWo / kStages) & 1;
    uint32_t wo = sm + kSlotWo * kStageBytes + (lin ^ (((lin >> 7) & 3) << 4));
    uint32_t lead = lane < 4, bv = sm + kOffQ + lane * 16;
    uint32_t* dst = g_out + ((10 * j + w) * kH + h) * 16 + 2 * r;
    pin(wo); pin(lead); pin(bv); pin(dst);

#pragma unroll 1
    for (uint32_t pass = 0; pass < 2; pass++) {
        uint32_t writer = pass && quad == 0;
        pin(writer);
        if (pass) bar_sync<kBarGate, 448>();
        uint32_t a[3][4][4];
        auto fetch = [&](int k) {
#pragma unroll
            for (int i = 0; i < 4; i++) ldsm4t(a[k][i], wo + k * kStageBytes + i * (16 * 320));
        };
#pragma unroll
        for (int k = 0; k < 2; k++) {
            if (pass) mbar_wait(full + 8 * (kSlotWo + k), parity);
            fetch(k);
        }
        float c[4][4];
#pragma unroll
        for (int k = 0; k < 4; k++) c[k][0] = c[k][1] = c[k][2] = c[k][3] = 0.f;
        uint4 b[6];
#pragma unroll
        for (int k = 0; k < 6; k++) b[k] = make_uint4(0, 0, 0, 0);

        bool have_tile = false;
        for (unsigned n = 0; !mbar_test(sm + kOffVecBar, 0) && pass; n++) {
            if (!have_tile && mbar_test(full + 8 * (kSlotWo + 2), parity)) {
                fetch(2);
                have_tile = true;
            }
            if (n > kSpinLimit) __trap();
        }
#pragma unroll
        for (int k = 0; k < 6; k++) lds128_if(b[k], bv + 128 * k, lead);
#pragma unroll
        for (int k = 0; k < 2; k++) {
            mma(c[0], a[k][0], b[2 * k].x, b[2 * k].y);
            mma(c[1], a[k][1], b[2 * k].z, b[2 * k].w);
            mma(c[2], a[k][2], b[2 * k + 1].x, b[2 * k + 1].y);
            mma(c[3], a[k][3], b[2 * k + 1].z, b[2 * k + 1].w);
        }
        if (!have_tile) {
            for (unsigned n = 0; !mbar_test(full + 8 * (kSlotWo + 2), parity) && pass; n++) if (n > kSpinLimit) __trap();
            fetch(2);
        }
        mma(c[0], a[2][0], b[4].x, b[4].y);
        mma(c[1], a[2][1], b[4].z, b[4].w);
        mma(c[2], a[2][2], b[5].x, b[5].y);
        mma(c[3], a[2][3], b[5].z, b[5].w);
        put2_if(dst, tagged((c[0][0] + c[1][0]) + (c[2][0] + c[3][0])), tagged((c[0][2] + c[1][2]) + (c[2][2] + c[3][2])), writer);
        if (fin < 0) continue;

        if (w < 8) {
            const uint32_t dl = ((mi >> 1) * 8 + lr) * 32 + (mi & 1) * 16;
            uint32_t tile = sm + kSlotDown * kStageBytes + w * (96 * 32) + (dl ^ (((dl >> 7) & 1) << 4));
            uint32_t part = sm + kOffPart + r * 32 + w * 4;
            pin(tile); pin(part);
#pragma unroll
            for (int k = 0; k < 6; k++) lds128_if(b[k], sm + kOffHid + (24 * (k / 3) + 3 * w + k % 3) * 64 + lane * 16, lead);
#pragma unroll
            for (int k = 0; k < 3; k++) c[k][0] = c[k][1] = c[k][2] = c[k][3] = 0.f;
#pragma unroll
            for (int k = 0; k < 2; k++) {
                for (unsigned n = 0; !mbar_test(full + 8 * (kSlotDown + k), parity) && pass; n++) if (n > kSpinLimit) __trap();
                uint32_t f[6][4];
#pragma unroll
                for (int i = 0; i < 6; i++) ldsm4t(f[i], tile + k * kStageBytes + i * 512);
#pragma unroll
                for (int i = 0; i < 3; i++) mma(c[i], f[2 * i], b[3 * k + i].x, b[3 * k + i].y);
#pragma unroll
                for (int i = 0; i < 3; i++) mma(c[i], f[2 * i + 1], b[3 * k + i].z, b[3 * k + i].w);
            }
            asm volatile("{\n.reg .pred p;\nsetp.eq.u32 p, %3, 0;\n@p st.shared.f32 [%0], %1;\n@p st.shared.f32 [%0 + 256], %2;\n}"
                         :: "r"(part), "f"(c[0][0] + c[1][0] + c[2][0]), "f"(c[0][2] + c[1][2] + c[2][2]), "r"(quad) : "memory");
            __syncwarp();
            if (lane == 0) mbar_arrive(sm + kOffPartBar);
        } else if (w == 9) {
            const int col = (lane & 15) / 2 + 8 * (lane & 1);
            uint32_t* src = g_out + fin * (kH * 16) + lane;
            uint32_t* used = (pass ? g_out + fin * (kH * 16) : g_sink) + 4 * lane;
            __nv_bfloat16* res = (pass ? out + 16 * fin : reinterpret_cast<__nv_bfloat16*>(g_sink)) + col;
            uint32_t part = sm + kOffPart + col * 32;
            pin(src); pin(used); pin(res); pin(part);
            auto gate = [&]() {
                const uint4 p0 = lds128(part), p1 = lds128(part + 16);
                const float d = ((__uint_as_float(p0.x) + __uint_as_float(p0.y)) + (__uint_as_float(p0.z) + __uint_as_float(p0.w))) +
                                ((__uint_as_float(p1.x) + __uint_as_float(p1.y)) + (__uint_as_float(p1.z) + __uint_as_float(p1.w)));
                return bf16r(silu(bf16r(d)));
            };
            uint32_t v[16];
#pragma unroll
            for (int i = 0; i < 16; i++) v[i] = pass ^ 1;
            float g = 0.f;
            bool have_g = false;
            const uint32_t start = clock_lo();
            for (unsigned n = 0;; n++) {
#pragma unroll
                for (int i = 0; i < 16; i++) peek(src + 32 * i, v[i]);
                if (!have_g && (mbar_test(sm + kOffPartBar, pass) || !pass)) {
                    g = gate();
                    have_g = pass;
                }
                uint32_t have = ~(uint32_t)((int)(clock_lo() - start) >> 31);
#pragma unroll
                for (int i = 0; i < 16; i++) have &= v[i];
                pin(have);
                if (__all_sync(~0u, have & 1)) break;
                if (n > kSpinLimit) __trap();
            }
            float sum[8];
#pragma unroll
            for (int i = 0; i < 8; i++) sum[i] = __uint_as_float(v[i]) + __uint_as_float(v[i + 8]);
            float s = ((sum[0] + sum[1]) + (sum[2] + sum[3])) + ((sum[4] + sum[5]) + (sum[6] + sum[7]));
            s = bf16r(s + __shfl_xor_sync(~0u, s, 16));
            if (!have_g) {
                for (unsigned n = 0; !mbar_test(sm + kOffPartBar, pass); n++) if (n > kSpinLimit) __trap();
                g = gate();
            }
            *res = __float2bfloat16_rn(xin + bf16r(s * g));
#pragma unroll
            for (int i = 0; i < 4; i++) put4(used + 128 * i, 0, 0, 0, 0);
        }
    }
}

__global__ void __launch_bounds__(kThreads, 1)
decode_block_kernel(const uint8_t* __restrict__ wq_bytes, const __nv_bfloat16* __restrict__ x, __nv_bfloat16* __restrict__ out,
                    const __grid_constant__ Maps maps) {
    if (threadIdx.x < 4 * 48) {
        constexpr int kPitch = kH * kDh * 2;
        const uint8_t* line = wq_bytes + ((160 * (blockIdx.x & 3) * kPitch + (blockIdx.x >> 2) * (kDh * 2)) +
                                          (threadIdx.x >> 2) * kPitch + (threadIdx.x & 3) * 128);
        asm volatile("prefetch.global.L2 [%0];" :: "l"(line) : "memory");
    }
    extern __shared__ __align__(1024) uint8_t smem[];
    const uint32_t sm = (uint32_t)__cvta_generic_to_shared(smem);
    const int w = threadIdx.x >> 5;
    const int h = blockIdx.x >> 2, j = blockIdx.x & 3;
    uint64_t pol;
    asm volatile("createpolicy.fractional.L2::evict_first.b64 %0, 1.0;" : "=l"(pol));
    uint32_t sm0 = sm;
    const CUtensorMap* wq = &maps.wq;
    pin(sm0);
    pin(wq);
    if (threadIdx.x == 128) {
        first_loads(wq, sm0, h, j, pol);
#pragma unroll
        for (int i = 0; i < kStages; i++) {
            if (i >= kLdGate) mbar_init(sm + kOffBar + 8 * i, 1);
            mbar_init(sm + kOffBar + 8 * (kStages + i), 5);
        }
        mbar_init(sm + kOffVecBar, 4);
        mbar_init(sm + kOffPartBar, 8);
        asm volatile("fence.mbarrier_init.release.cluster;" ::: "memory");
    }
    __syncwarp();
    if (w == 4) {
        bar_arrive<kBarMonitor, 64>();
        bar_arrive<kBarInit, 480>();
        if (threadIdx.x == 128) producer(maps, sm, h, j, pol);
    } else if (w == 5) {
        bar_sync<kBarMonitor, 64>();
        if (threadIdx.x == 160) monitor(sm, h);
    } else if (w < 4) {
        consumer(x, smem, sm, j);
    } else {
        projector(x, out, smem, sm, h, j);
    }
}

typedef CUresult (*EncodeFn)(CUtensorMap*, CUtensorMapDataType, cuuint32_t, void*, const cuuint64_t*, const cuuint64_t*,
                             const cuuint32_t*, const cuuint32_t*, CUtensorMapInterleave, CUtensorMapSwizzle,
                             CUtensorMapL2promotion, CUtensorMapFloatOOBfill);

void encode3(EncodeFn enc, CUtensorMap* tm, const void* p, uint64_t rows, uint64_t cols, uint32_t inner, uint32_t segs,
             uint32_t box_rows, CUtensorMapSwizzle sw,
             CUtensorMapL2promotion promo = CU_TENSOR_MAP_L2_PROMOTION_NONE) {
    const cuuint64_t dims[3] = {inner, cols / inner, rows};
    const cuuint64_t strides[2] = {inner * 2ull, cols * 2ull};
    const cuuint32_t box[3] = {inner, segs, box_rows};
    const cuuint32_t es[3] = {1, 1, 1};
    enc(tm, CU_TENSOR_MAP_DATA_TYPE_BFLOAT16, 3, const_cast<void*>(p), dims, strides, box, es,
        CU_TENSOR_MAP_INTERLEAVE_NONE, sw, promo, CU_TENSOR_MAP_FLOAT_OOB_FILL_NONE);
}

}

extern "C" void kernel_launch(void* const* d_in, const int* in_sizes, int n_in, void* d_out, int out_size) {
    (void)in_sizes; (void)n_in; (void)out_size;
    static EncodeFn enc = nullptr;
    if (!enc) {
        void* fn = nullptr;
        cudaDriverEntryPointQueryResult qr;
        cudaGetDriverEntryPoint("cuTensorMapEncodeTiled", &fn, cudaEnableDefault, &qr);
        enc = (EncodeFn)fn;
        cudaFuncSetAttribute(decode_block_kernel, cudaFuncAttributeMaxDynamicSharedMemorySize, kSmemBytes);
    }
    Maps maps;
    encode3(enc, &maps.k, d_in[1], (uint64_t)kH * kSk, kDh, 64, 3, 64, CU_TENSOR_MAP_SWIZZLE_128B);
    encode3(enc, &maps.v, d_in[2], (uint64_t)kH * kSk, kDh, 64, 3, 64, CU_TENSOR_MAP_SWIZZLE_128B);
    encode3(enc, &maps.wq, d_in[3], kD, kH * kDh, 64, 3, 64, CU_TENSOR_MAP_SWIZZLE_128B);
    encode3(enc, &maps.wq_tail, d_in[3], kD, kH * kDh, 64, 3, 32, CU_TENSOR_MAP_SWIZZLE_128B);
    encode3(enc, &maps.wo, d_in[4], kH * kDh, kD, 32, 5, 64, CU_TENSOR_MAP_SWIZZLE_64B);
    encode3(enc, &maps.gate, d_in[6], kD, kF, 48, 1, 160, CU_TENSOR_MAP_SWIZZLE_NONE);
    encode3(enc, &maps.up, d_in[7], kD, kF, 48, 1, 160, CU_TENSOR_MAP_SWIZZLE_NONE);
    encode3(enc, &maps.down, d_in[8], kF, kD, 16, 1, 256, CU_TENSOR_MAP_SWIZZLE_32B, CU_TENSOR_MAP_L2_PROMOTION_L2_256B);
    decode_block_kernel<<<kCtas, kThreads, kSmemBytes>>>(
        (const uint8_t*)d_in[3], (const __nv_bfloat16*)d_in[0], (__nv_bfloat16*)d_out, maps);
}
```

```cpp
#include <cuda_runtime.h>
#include <cuda_bf16.h>
#include <cuda.h>
#include <stdint.h>

namespace {

constexpr int kH = 32, kSk = 4096, kDh = 192, kD = 640, kF = 1536;
constexpr int kCtas = 128, kThreads = 512;
constexpr int kFinishers = kD / 16, kFirstFinisher = kCtas - kFinishers;
constexpr int kStageBytes = 24576, kStages = 9;
constexpr int kTiles = 16;
constexpr int kLdGate = 3, kLdK = 5, kLdV = kLdK + kTiles, kLdWo = kLdV + kTiles;
constexpr int kLdDown = kLdWo + 3, kLoads = kLdDown + 2;

__host__ __device__ constexpr int load_bytes(int i) {
    return i == 2 ? kStageBytes / 2 : i >= kLdGate && i < kLdK ? 160 * 96 : i >= kLdWo && i < kLdDown ? 64 * 320 : kStageBytes;
}
__device__ __forceinline__ int gate_tile(int h) { return 2 * (h >> 2) + 1; }

constexpr int kUnit = 512, kWindow = 216, kWindowEnd = 128, kStagger = 192, kFinisherLead = 2048;
constexpr int kLdPaced = 8, kDepth = 3;
__host__ __device__ constexpr int units_through(int i) {
    int sum = 0;
    for (int k = 0; k <= i; k++) sum += load_bytes(k) / kUnit;
    return sum;
}
constexpr int kLaunchUnits = 1 << 18;
constexpr int kPadUnits = kLaunchUnits - kCtas * units_through(kLdDown - 1) - kFinishers * 2 * (kStageBytes / kUnit);
static_assert(kPadUnits >= 0, "padding");

constexpr int kOffScore = kStages * kStageBytes;
constexpr int kOffP = kOffScore + 4096;
constexpr int kOffXn = kOffP + 4096;
constexpr int kOffQ = kOffXn + 640;
constexpr int kOffSend = kOffQ + 768;
constexpr int kOffRed = kOffSend + 192;
constexpr int kOffTag = kOffRed + 44;
constexpr int kOffSide = kOffTag + 4;
constexpr int kOffTrip = kOffSide + 16;
constexpr int kOffBar = kOffTrip + 16;
constexpr int kOffVecBar = kOffBar + 16 * kStages;
constexpr int kOffPartBar = kOffVecBar + 8;
constexpr int kSmemBytes = kOffPartBar + 8;
constexpr int kOffHid = kOffScore;
constexpr int kOffPart = kOffHid + 2 * kF;

constexpr int kBoxFfn = 576, kBoxStat = 960, kBoxWords = 1024;
constexpr int kCopy = 1024, kTripLine = 640;
constexpr int kAtLanded = kCtas + kFinishers, kAtBox = kAtLanded + 1, kAtHid = kAtBox + kCtas * kBoxWords / (2 * kCopy);
constexpr unsigned kSpinLimit = 1u << 24;

constexpr int kBarMain = 1, kBarInit = 2, kBarMonitor = 3, kBarStat = 4, kBarGate = 5, kBarScale = 6, kBarProj = 7;

struct Maps { CUtensorMap wq, wq_tail, gate, up, k, v, down, wo; };

__device__ __align__(128) uint32_t g_pairs[(kAtHid + kFinishers + 1) * 2 * kCopy];
__device__ __align__(128) uint32_t g_sink[8];

__device__ __forceinline__ uint32_t* box_pair(int i) {
    constexpr uintptr_t kMask = 8 * kCopy - 1;
    return reinterpret_cast<uint32_t*>((reinterpret_cast<uintptr_t>(g_pairs) + kMask) & ~kMask) + i * (2 * kCopy);
}
__device__ __forceinline__ uint32_t* landed_units() { return box_pair(kAtLanded) + kCopy; }
__device__ __forceinline__ uint32_t* mailbox(int cta) { return box_pair(kAtBox) + cta * kBoxWords; }
__device__ __forceinline__ uint32_t* hidden(int fin) { return box_pair(kAtHid + fin); }

__device__ __forceinline__ void mbar_init(uint32_t bar, uint32_t cnt) {
    asm volatile("mbarrier.init.shared::cta.b64 [%0], %1;" :: "r"(bar), "r"(cnt) : "memory");
}
__device__ __forceinline__ void mbar_expect_tx(uint32_t bar, uint32_t bytes) {
    asm volatile("mbarrier.arrive.expect_tx.shared::cta.b64 _, [%0], %1;" :: "r"(bar), "r"(bytes) : "memory");
}
__device__ __forceinline__ void mbar_arrive(uint32_t bar) {
    asm volatile("mbarrier.arrive.shared::cta.b64 _, [%0];" :: "r"(bar) : "memory");
}
__device__ __forceinline__ bool mbar_try(uint32_t bar, uint32_t parity) {
    uint32_t ok;
    asm volatile("{\n.reg .pred p;\nmbarrier.try_wait.parity.shared::cta.b64 p, [%1], %2;\nselp.u32 %0, 1, 0, p;\n}"
                 : "=r"(ok) : "r"(bar), "r"(parity) : "memory");
    return ok;
}
__device__ __forceinline__ bool mbar_test(uint32_t bar, uint32_t parity) {
    uint32_t ok;
    asm volatile("{\n.reg .pred p;\nmbarrier.test_wait.parity.shared::cta.b64 p, [%1], %2;\nselp.u32 %0, 1, 0, p;\n}"
                 : "=r"(ok) : "r"(bar), "r"(parity) : "memory");
    return ok;
}
__device__ __forceinline__ void mbar_wait(uint32_t bar, uint32_t parity) {
    unsigned n = 0;
    while (!mbar_try(bar, parity)) { if (++n > kSpinLimit) __trap(); }
}
__device__ __forceinline__ void tma3(uint32_t dst, const CUtensorMap* tm, int c0, int c1, int c2, uint32_t bar, uint64_t pol) {
    asm volatile("cp.async.bulk.tensor.3d.shared::cluster.global.mbarrier::complete_tx::bytes.L2::cache_hint"
                 " [%0], [%1, {%3, %4, %5}], [%2], %6;"
                 :: "r"(dst), "l"(tm), "r"(bar), "r"(c0), "r"(c1), "r"(c2), "l"(pol) : "memory");
}
__device__ __forceinline__ void ldsm4(uint32_t (&a)[4], uint32_t addr) {
    asm volatile("ldmatrix.sync.aligned.m8n8.x4.shared.b16 {%0,%1,%2,%3}, [%4];"
                 : "=r"(a[0]), "=r"(a[1]), "=r"(a[2]), "=r"(a[3]) : "r"(addr) : "memory");
}
__device__ __forceinline__ void ldsm4t(uint32_t (&a)[4], uint32_t addr) {
    asm volatile("ldmatrix.sync.aligned.m8n8.x4.trans.shared.b16 {%0,%1,%2,%3}, [%4];"
                 : "=r"(a[0]), "=r"(a[1]), "=r"(a[2]), "=r"(a[3]) : "r"(addr) : "memory");
}
__device__ __forceinline__ void mma(float (&c)[4], const uint32_t (&a)[4], uint32_t b0, uint32_t b1) {
    asm("mma.sync.aligned.m16n8k16.row.col.f32.bf16.bf16.f32 {%0,%1,%2,%3}, {%4,%5,%6,%7}, {%8,%9}, {%0,%1,%2,%3};"
                 : "+f"(c[0]), "+f"(c[1]), "+f"(c[2]), "+f"(c[3])
                 : "r"(a[0]), "r"(a[1]), "r"(a[2]), "r"(a[3]), "r"(b0), "r"(b1));
}
__device__ __forceinline__ uint4 lds128(uint32_t addr) {
    uint4 v;
    asm volatile("ld.shared.v4.u32 {%0,%1,%2,%3}, [%4];" : "=r"(v.x), "=r"(v.y), "=r"(v.z), "=r"(v.w) : "r"(addr) : "memory");
    return v;
}
__device__ __forceinline__ void lds128_if(uint4& v, uint32_t addr, uint32_t p) {
    asm volatile("{\n.reg .pred p;\nsetp.ne.u32 p, %5, 0;\n@p ld.shared.v4.u32 {%0,%1,%2,%3}, [%4];\n}"
                 : "+r"(v.x), "+r"(v.y), "+r"(v.z), "+r"(v.w) : "r"(addr), "r"(p) : "memory");
}
__device__ __forceinline__ void pin(uint32_t& v) { asm volatile("" : "+r"(v)); }
__device__ __forceinline__ void pin(float& v) { asm volatile("" : "+f"(v)); }
template <typename T> __device__ __forceinline__ void pin(T*& p) { asm volatile("" : "+l"(p)); }
template <int kId, int kCount> __device__ __forceinline__ void bar_sync() {
    asm volatile("bar.sync %0, %1;" :: "n"(kId), "n"(kCount) : "memory");
}
template <int kId, int kCount> __device__ __forceinline__ void bar_arrive() {
    asm volatile("bar.arrive %0, %1;" :: "n"(kId), "n"(kCount) : "memory");
}

__device__ __forceinline__ uint32_t tagged(float v) { return __float_as_uint(v) | 1u; }
__device__ __forceinline__ float untagged(uint32_t w) { return __uint_as_float(w & ~1u); }
__device__ __forceinline__ void put2(uint32_t* p, uint32_t a, uint32_t b) {
    asm volatile("st.relaxed.gpu.global.b64 [%0], %1;" :: "l"(p), "l"(((uint64_t)b << 32) | a) : "memory");
}
__device__ __forceinline__ void put2_if(uint32_t* p, uint32_t a, uint32_t b, uint32_t pred) {
    asm volatile("{\n.reg .pred p;\nsetp.ne.u32 p, %2, 0;\n@p st.relaxed.gpu.global.b64 [%0], %1;\n}"
                 :: "l"(p), "l"(((uint64_t)b << 32) | a), "r"(pred) : "memory");
}
__device__ __forceinline__ void put4(uint32_t* p, uint32_t a, uint32_t b, uint32_t c, uint32_t d) {
    asm volatile("st.relaxed.gpu.global.v4.b32 [%0], {%1, %2, %3, %4};" :: "l"(p), "r"(a), "r"(b), "r"(c), "r"(d) : "memory");
}
__device__ __forceinline__ void take(uint32_t* p, uint32_t& w) {
    asm volatile("atom.relaxed.gpu.global.exch.b32 %0, [%1], 0;" : "=r"(w) : "l"(p) : "memory");
}
__device__ __forceinline__ void take(uint32_t* p, uint64_t& w) {
    asm volatile("atom.relaxed.gpu.global.exch.b64 %0, [%1], 0;" : "=l"(w) : "l"(p) : "memory");
}
template <typename Word, int kN, typename Addr>
__device__ __forceinline__ void gather(Addr addr, Word (&w)[kN], unsigned mask, unsigned sleep_ns) {
#pragma unroll
    for (int i = 0; i < kN; i++) w[i] = 0;
    for (unsigned n = 0;; n++) {
        Word t[kN];
#pragma unroll
        for (int i = 0; i < kN; i++) take(addr(i), t[i]);
        uint32_t have = ~0u;
#pragma unroll
        for (int i = 0; i < kN; i++) {
            w[i] |= t[i];
            have &= (uint32_t)w[i];
        }
        pin(have);
        if (__all_sync(mask, have & 1)) break;
        if (n > kSpinLimit) __trap();
        if (sleep_ns) __nanosleep(sleep_ns);
    }
}
__device__ __forceinline__ void peek(const uint32_t* p, uint32_t& w, uint32_t tag) {
    asm volatile("{\n.reg .pred p;\n.reg .b32 t;\n"
                 "and.b32 t, %0, %2;\nsetp.eq.u32 p, t, 0;\n"
                 "@p ld.relaxed.gpu.global.b32 %0, [%1];\n}"
                 : "+r"(w) : "l"(p), "r"(tag) : "memory");
}
__device__ __forceinline__ uint32_t clock_lo() {
    uint32_t c;
    asm volatile("mov.u32 %0, %%clock;" : "=r"(c) :: "memory");
    return c;
}
__device__ __forceinline__ void spin(uint32_t cycles) {
    const uint32_t start = clock_lo();
    while (clock_lo() - start < cycles) {}
}
__device__ __forceinline__ uint32_t round_trips(uint32_t* line, int lane) {
    if (lane < 8) put4(line + 4 * lane, 0, 0, 0, 0);
    __syncwarp();
    uint32_t sum = 0, zero = 0;
#pragma unroll 1
    for (int i = 0; i < 4; i++) {
        const uint32_t start = clock_lo();
        uint32_t end;
        asm volatile("ld.relaxed.gpu.global.b32 %0, [%1];" : "=r"(end) : "l"(line + zero) : "memory");
        asm volatile("{\n.reg .pred p;\nsetp.ne.u32 p, %0, 0;\n@p trap;\nmov.u32 %0, %%clock;\n}" : "+r"(end) :: "memory");
        zero = (end - start) >> 31;
        if (i) sum += end - start;
    }
    return sum;
}

__device__ __forceinline__ float bf16r(float v) { return __bfloat162float(__float2bfloat16_rn(v)); }
__device__ __forceinline__ float bf_lo(uint32_t u) { return __uint_as_float(u << 16); }
__device__ __forceinline__ float bf_hi(uint32_t u) { return __uint_as_float(u & 0xffff0000u); }
__device__ __forceinline__ uint32_t pack_bf16(float lo, float hi) {
    __nv_bfloat162 t = __floats2bfloat162_rn(lo, hi);
    return *reinterpret_cast<uint32_t*>(&t);
}
__device__ __forceinline__ float silu(float v) { return __fdividef(v, 1.0f + __expf(-v)); }
__device__ __forceinline__ float pick3(int s, float a, float b, float c) { return s == 0 ? a : (s == 1 ? b : c); }

__device__ __forceinline__ int bvec_off(int mt, int r) {
    return (mt >> 1) * 128 + (r >> 1) * 16 + (mt & 1) * 8 + (r & 1) * 2;
}

struct Ring {
    uint32_t full, empty;
    int slot; uint32_t phase;
    __device__ __forceinline__ uint32_t acquire(uint32_t ring) {
        mbar_wait(full + 8 * slot, phase);
        return ring + slot * kStageBytes;
    }
    __device__ __forceinline__ void release(int lane) {
        __syncwarp();
        if (lane == 0) mbar_arrive(empty + 8 * slot);
        skip();
    }
    __device__ __forceinline__ void skip() {
        if (++slot == kStages) { slot = 0; phase ^= 1; }
    }
};

__device__ __forceinline__ void gemv384(float (&acc)[3][4], uint32_t tile, const uint32_t (&off)[3], uint32_t bvec) {
    const uint4 b = lds128(bvec);
    uint32_t a[2][3][4];
#pragma unroll
    for (int ks = 0; ks < 2; ks++)
#pragma unroll
        for (int m = 0; m < 3; m++) ldsm4t(a[ks][m], tile + off[m] + ks * (16 * 384));
#pragma unroll
    for (int m = 0; m < 3; m++) mma(acc[m], a[0][m], b.x, b.y);
#pragma unroll
    for (int m = 0; m < 3; m++) mma(acc[m], a[1][m], b.z, b.w);
}

__device__ __forceinline__ void zero3(float (&acc)[3][4]) {
#pragma unroll
    for (int m = 0; m < 3; m++)
#pragma unroll
        for (int i = 0; i < 4; i++) acc[m][i] = 0.f;
}

__device__ __forceinline__ void first_loads(const CUtensorMap* wq, uint32_t sm, int h, int j, uint64_t pol) {
#pragma unroll
    for (int i = 0; i < kLdGate; i++) {
        const uint32_t bar = sm + kOffBar + 8 * i;
        mbar_init(bar, 1);
        asm volatile("fence.mbarrier_init.release.cluster;" ::: "memory");
        tma3(sm + i * kStageBytes, wq + (i == 2), 0, 3 * h, 160 * j + 64 * i, bar, pol);
        mbar_expect_tx(bar, load_bytes(i));
    }
}

__device__ __forceinline__ void producer(const Maps& maps, uint32_t sm, int h, int j, uint64_t pol) {
    const uint32_t full = sm + kOffBar, empty = full + 8 * kStages;
    const int kvrow = h * kSk + j * (kTiles * 64);
    int landed = 0, need = kCtas * (units_through(kLdGate - 1) - kWindow) - h * kStagger - (blockIdx.x >= kFirstFinisher ? kFinisherLead : 0);
    static_assert(kCtas * (units_through(kLdPaced) - kWindow) > kH * kStagger + kFinisherLead, "load kLdPaced reads the counter");
    unsigned total = 0;
    int slot = kLdGate; uint32_t phase = 1;
    const int gate = kLdGate + gate_tile(h);
    const int fin = blockIdx.x - kFirstFinisher, loads = fin >= 0 ? kLoads : kLdDown;
#pragma unroll 1
    for (int i = kLdGate; i < loads; i++) {
        const uint32_t bar = full + 8 * slot, dst = sm + slot * kStageBytes;
        const CUtensorMap* tm; int c1, c2; uint32_t bytes;
        if (i < gate)          { tm = &maps.k;    c1 = 0;     c2 = kvrow + 64 * (i - kLdGate);    bytes = kStageBytes; }
        else if (i < gate + 2) { tm = &maps.gate + (i - gate); c1 = h; c2 = 160 * j;              bytes = 160 * 96; }
        else if (i < kLdV)     { tm = &maps.k;    c1 = 0;     c2 = kvrow + 64 * (i - kLdK);       bytes = kStageBytes; }
        else if (i < kLdWo)    { tm = &maps.v;    c1 = 0;     c2 = kvrow + 64 * (i - kLdV);       bytes = kStageBytes; }
        else if (i < kLdDown)  { tm = &maps.wo;   c1 = 5 * j; c2 = kDh * h + 64 * (i - kLdWo);    bytes = 64 * 320; }
        else                   { tm = &maps.down; c1 = fin;   c2 = 768 * (i - kLdDown);           bytes = kStageBytes; }
        need += bytes * kCtas / kUnit;
        if (i >= kLdDown) need = kCtas * (units_through(kLdDown - 1) - kWindowEnd) - kFinisherLead;
        if (i == kLdWo) need += kCtas * (kWindow - kWindowEnd);
        if (i > kLdWo && i < kLdDown) need += (h - kH / 2) * (kStagger / 2);
        if (i >= kStages) mbar_wait(empty + 8 * slot, phase);
        if (i < kLdPaced) mbar_wait(full + 8 * (i - kDepth), 0);
        for (unsigned n = 0; landed < need && i >= kLdPaced; n++) {
            asm volatile("ld.relaxed.gpu.global.u32 %0, [%1];" : "=r"(total) : "l"(landed_units()) : "memory");
            landed = (int)(total & (kLaunchUnits - 1));
            if (n > kSpinLimit) __trap();
        }
        mbar_expect_tx(bar, bytes);
        tma3(dst, tm, 0, c1, c2, bar, pol);
        if (i == kLdPaced) asm volatile("st.shared.u32 [%0], %1;" :: "r"(sm + kOffTag), "r"(1 + total / kLaunchUnits % 2) : "memory");
        if (i >= kLdDown) {
            tma3(dst + 8192, tm, 0, c1, c2 + 256, bar, pol);
            tma3(dst + 16384, tm, 0, c1, c2 + 512, bar, pol);
        }
        if (++slot == kStages) { slot = 0; phase ^= 1; }
    }
    if (blockIdx.x == kCtas - 1)
        asm volatile("red.relaxed.gpu.global.add.u32 [%0], %1;" :: "l"(landed_units()), "r"(kPadUnits) : "memory");
}

__device__ __forceinline__ void monitor(uint32_t sm, int h) {
    const int gate = kLdGate + gate_tile(h);
    const uint32_t full = sm + kOffBar, empty = full + 8 * kStages;
    int slot = 0; uint32_t phase = 0;
    const int loads = blockIdx.x >= kFirstFinisher ? kLoads : kLdDown;
#pragma unroll 1
    for (int i = 0; i < loads; i++) {
        mbar_wait(full + 8 * slot, phase);
        const int k = i < kLdGate || i >= kLdV ? i : i == gate || i == gate + 1 ? kLdGate : kLdK;
        const int units = load_bytes(k) / kUnit;
        asm volatile("red.relaxed.gpu.global.add.u32 [%0], %1;" :: "l"(landed_units()), "r"(units) : "memory");
        mbar_arrive(empty + 8 * slot);
        if (++slot == kStages) { slot = 0; phase ^= 1; }
    }
}

__device__ __forceinline__ void layer_norm(const __nv_bfloat16* __restrict__ x, uint8_t* smem, int j) {
    const int tid = threadIdx.x, lane = tid & 31;
    const uint4* x4 = reinterpret_cast<const uint4*>(x);
    uint4 xv[3];
    xv[0] = __ldg(x4 + lane);
    xv[1] = __ldg(x4 + 32 + lane);
    xv[2] = lane < 16 ? __ldg(x4 + 64 + lane) : make_uint4(0, 0, 0, 0);
    uint32_t xs = 0;
    if (tid < 80) xs = __ldg(reinterpret_cast<const uint32_t*>(x) + j * 80 + tid);

    for (int i = tid; i < (kOffRed - kOffXn) / 16; i += 128)
        *reinterpret_cast<uint4*>(smem + kOffXn + i * 16) = make_uint4(0, 0, 0, 0);

    float sum = 0.f;
#pragma unroll
    for (int i = 0; i < 3; i++) {
        const uint32_t u[4] = {xv[i].x, xv[i].y, xv[i].z, xv[i].w};
#pragma unroll
        for (int k = 0; k < 4; k++) sum += bf_lo(u[k]) + bf_hi(u[k]);
    }
#pragma unroll
    for (int s = 16; s > 0; s >>= 1) sum += __shfl_xor_sync(~0u, sum, s);
    const float mean = sum * (1.0f / kD);
    float sq = 0.f;
#pragma unroll
    for (int i = 0; i < 3; i++) {
        const uint32_t u[4] = {xv[i].x, xv[i].y, xv[i].z, xv[i].w};
        if (i < 2 || lane < 16) {
#pragma unroll
            for (int k = 0; k < 4; k++) {
                const float a = bf_lo(u[k]) - mean, b = bf_hi(u[k]) - mean;
                sq += a * a + b * b;
            }
        }
    }
#pragma unroll
    for (int s = 16; s > 0; s >>= 1) sq += __shfl_xor_sync(~0u, sq, s);
    const float mean_b = bf16r(mean);
    const float den = bf16r(__fsqrt_rn(bf16r(bf16r(sq * (1.0f / kD)) + 1e-5f)));
    bar_sync<kBarMain, 128>();
    if (tid < 80) {
        const int k = 2 * tid;
        const float a = __fdividef(bf16r(bf_lo(xs) - mean_b), den), b = __fdividef(bf16r(bf_hi(xs) - mean_b), den);
        const int off = (k >> 5) * 128 + ((k & 7) >> 1) * 16 + ((k >> 4) & 1) * 8 + ((k >> 3) & 1) * 4;
        *reinterpret_cast<uint32_t*>(smem + kOffXn + off) = pack_bf16(a, b);
    }
}

__device__ __forceinline__ void gate_up(Ring& ring, uint32_t sm) {
    const int lane = threadIdx.x & 31, w = threadIdx.x >> 5;
    const int quad = lane & 3, r = lane >> 2, mi = lane >> 3, lr = lane & 7;
    const uint32_t bsel = (r & 1) * 64 + quad * 16;
    const uint32_t off = ((mi >> 1) * 8 + lr) * 96 + (2 * w + (mi & 1)) * 16;
    uint32_t g0 = 0, g1 = 0;
#pragma unroll 1
    for (int g = 0; g < 2; g++) {
        const uint32_t tile = ring.acquire(sm);
        if (w < 3) {
            float c[4] = {0.f, 0.f, 0.f, 0.f};
#pragma unroll
            for (int kb = 0; kb < 5; kb++) {
                const uint4 b = lds128(sm + kOffXn + kb * 128 + bsel);
                uint32_t a0[4], a1[4];
                ldsm4t(a0, tile + off + kb * (32 * 96));
                ldsm4t(a1, tile + off + kb * (32 * 96) + 16 * 96);
                mma(c, a0, b.x, b.y);
                mma(c, a1, b.z, b.w);
            }
            if (g == 0) { g0 = tagged(c[0]); g1 = tagged(c[2]); }
            else put4(mailbox(blockIdx.x ^ quad) + kBoxFfn + 96 * quad + 4 * (8 * w + r), g0, tagged(c[0]), g1, tagged(c[2]));
        }
        ring.release(lane);
    }
}

__device__ __forceinline__ float scores_softmax(Ring& ring, uint8_t* smem, uint32_t sm) {
    const int tid = threadIdx.x, lane = tid & 31, w = tid >> 5;
    const int quad = lane & 3, r = lane >> 2, mi = lane >> 3, lr = lane & 7;
    float* score = reinterpret_cast<float*>(smem + kOffScore);
    float* red = reinterpret_cast<float*>(smem + kOffRed);
    uint32_t qf[24];
#pragma unroll
    for (int kb = 0; kb < 6; kb++) {
        const uint4 b = lds128(sm + kOffQ + kb * 128 + quad * 16);
        qf[4 * kb] = b.x; qf[4 * kb + 1] = b.y; qf[4 * kb + 2] = b.z; qf[4 * kb + 3] = b.w;
    }
    const int row = 16 * w + (mi & 1) * 8 + lr;
    uint32_t offk[3];
#pragma unroll
    for (int seg = 0; seg < 3; seg++)
        offk[seg] = row * 384 + seg * 128 + (((mi >> 1) ^ ((3 * row + seg) & 7)) << 4);
    const float scale = 0.07216878364870323f;
    float mx = -INFINITY;
#pragma unroll 1
    for (int t = 0; t < kTiles; t++) {
        if (t == gate_tile(blockIdx.x >> 2)) gate_up(ring, sm);
        const uint32_t tile = ring.acquire(sm);
        float c0[4] = {0.f, 0.f, 0.f, 0.f}, c1[4] = {0.f, 0.f, 0.f, 0.f};
        uint32_t a[12][4];
#pragma unroll
        for (int ks = 0; ks < 12; ks++) ldsm4(a[ks], tile + (offk[ks >> 2] ^ ((ks & 3) << 5)));
#pragma unroll
        for (int ks = 0; ks < 12; ks += 2) {
            mma(c0, a[ks], qf[2 * ks], qf[2 * ks + 1]);
            mma(c1, a[ks + 1], qf[2 * ks + 2], qf[2 * ks + 3]);
        }
        ring.release(lane);
        const float s = bf16r(bf16r((quad & 1) ? c0[2] + c1[2] : c0[0] + c1[0]) * scale);
        mx = fmaxf(mx, s);
        if (quad < 2) score[t * 64 + 16 * w + quad * 8 + r] = s;
    }
#pragma unroll
    for (int s = 16; s > 0; s >>= 1) mx = fmaxf(mx, __shfl_xor_sync(~0u, mx, s));
    if (lane == 0) red[w] = mx;
    bar_sync<kBarMain, 128>();
    mx = fmaxf(fmaxf(red[0], red[1]), fmaxf(red[2], red[3]));

    float lsum = 0.f;
    const int blk = tid >> 2;
    uint32_t hi[4], lo[4];
#pragma unroll
    for (int i = 0; i < 4; i++) {
        const float2 s = *reinterpret_cast<const float2*>(score + blk * 32 + i * 8 + 2 * quad);
        const float e0 = __expf(s.x - mx), e1 = __expf(s.y - mx);
        lsum += e0 + e1;
        hi[i] = pack_bf16(e0, e1);
        lo[i] = pack_bf16(e0 - bf_lo(hi[i]), e1 - bf_hi(hi[i]));
    }
    *reinterpret_cast<uint4*>(smem + kOffP + blk * 128 + quad * 16) = make_uint4(hi[0], hi[1], hi[2], hi[3]);
    *reinterpret_cast<uint4*>(smem + kOffP + blk * 128 + 64 + quad * 16) = make_uint4(lo[0], lo[1], lo[2], lo[3]);
#pragma unroll
    for (int s = 16; s > 0; s >>= 1) lsum += __shfl_xor_sync(~0u, lsum, s);
    if (lane == 0) red[4 + w] = lsum;
    return mx;
}

__device__ __forceinline__ void consumer(const __nv_bfloat16* __restrict__ x, uint8_t* smem, uint32_t sm, int j) {
    const int tid = threadIdx.x, lane = tid & 31, w = tid >> 5;
    const int quad = lane & 3, r = lane >> 2, mi = lane >> 3, lr = lane & 7;
    const int cta = blockIdx.x;
    float* red = reinterpret_cast<float*>(smem + kOffRed);

    layer_norm(x, smem, j);
    bar_sync<kBarInit, 480>();

    Ring ring{sm + kOffBar, sm + kOffBar + 8 * kStages, 0, 0};
    const uint32_t bsel = (r & 1) * 64 + quad * 16;
    const int frow = (mi >> 1) * 8 + lr;
    uint32_t off384[3];
#pragma unroll
    for (int m = 0; m < 3; m++) {
        const int chunk = 2 * (3 * w + m) + (mi & 1), seg = chunk >> 3;
        off384[m] = frow * 384 + seg * 128 + (((chunk & 7) ^ ((3 * frow + seg) & 7)) << 4);
    }

#pragma unroll 1
    for (int pass = 0; pass < 2; pass++) {
        const int mt = 3 * w + quad, pitch = pass ? 2 * kCopy : kBoxWords;
        uint32_t* boxes = (pass ? box_pair(0) : mailbox(0)) + 16 * mt + 2 * r;
        uint32_t* send[3];
#pragma unroll
        for (int i = 0; i < 3; i++) {
            send[i] = boxes + (cta ^ (i + 1)) * pitch + 192 * i;
            pin(send[i]);
        }
        uint32_t* recv = boxes + cta * pitch;
        uint32_t vec = sm + kOffQ + bvec_off(mt, r);
        pin(recv);
        pin(vec);

        float acc[3][4];
        zero3(acc);
        const int halves = pass ? 2 * kTiles : 5;
        uint32_t bv = sm + (pass ? kOffP : kOffXn) + bsel;
#pragma unroll 1
        for (int t = 0; t < halves; t += 2) {
            const uint32_t tile = ring.acquire(sm);
            gemv384(acc, tile, off384, bv);
            if (t + 1 < halves) gemv384(acc, tile + 32 * 384, off384, bv + 128);
            ring.release(lane);
            bv += 256;
        }
        float f = 1.f;
        if (pass) {
            bar_arrive<kBarGate, 448>();
            bar_sync<kBarScale, 160>();
            f = red[8];
            const uint4 side = lds128(sm + kOffSide);
            recv += side.x; send[0] += side.y; send[1] += side.z; send[2] += side.w;
        }

        const uint32_t a = tagged(f * pick3(quad, acc[0][0] + acc[0][1], acc[1][0] + acc[1][1], acc[2][0] + acc[2][1]));
        const uint32_t b = tagged(f * pick3(quad, acc[0][2] + acc[0][3], acc[1][2] + acc[1][3], acc[2][2] + acc[2][3]));
        if (quad < 3) {
#pragma unroll
            for (int i = 0; i < 3; i++) put2(send[i], a, b);
        }
        __syncwarp();
        uint64_t v[3];
        v[0] = v[1] = v[2] = 0;
        if (!pass) __nanosleep(600);
        spin(1000);
        if (quad < 3) gather([&](int i) { return recv + 192 * i; }, v, 0x77777777u, pass ? 0 : 500);
        __syncwarp();
        const uint32_t s0 = pack_bf16((untagged(a) + untagged((uint32_t)v[0])) + (untagged((uint32_t)v[1]) + untagged((uint32_t)v[2])), 0.f);
        const uint32_t s1 = pack_bf16((untagged(b) + untagged((uint32_t)(v[0] >> 32))) +
                                      (untagged((uint32_t)(v[1] >> 32)) + untagged((uint32_t)(v[2] >> 32))), 0.f);
        asm volatile("{\n.reg .pred p;\nsetp.ne.u32 p, %3, 3;\n@p st.shared.u16 [%0], %1;\n@p st.shared.u16 [%0 + 4], %2;\n}"
                     :: "r"(vec), "h"((uint16_t)s0), "h"((uint16_t)s1), "r"(quad) : "memory");
        __syncwarp();
        if (pass && lane == 0) mbar_arrive(sm + kOffVecBar);
        if (pass) break;
        bar_sync<kBarMain, 128>();
        const float mx = scores_softmax(ring, smem, sm);
        bar_sync<kBarMain, 128>();
        if (w == 0) {
            uint32_t trip0, trip1;
            asm volatile("ld.volatile.shared.v2.u32 {%0, %1}, [%2];" : "=r"(trip0), "=r"(trip1) : "r"(sm + kOffTrip) : "memory");
            const uint32_t sum = tagged((red[4] + red[5]) + (red[6] + red[7])) ^ __shfl_sync(~0u, trip0 <= trip1, 0);
            if (tid < 4) put2(mailbox(cta ^ tid) + kBoxStat + 8 * tid, tagged(mx), sum);
            __syncwarp();
            bar_arrive<kBarStat, 160>();
        }
    }
}

__device__ __forceinline__ void projector(const __nv_bfloat16* __restrict__ x, __nv_bfloat16* __restrict__ out, uint8_t* smem,
                                          uint32_t sm, int h, int j) {
    const int t = threadIdx.x - 192, lane = t & 31, w = t >> 5;
    const int quad = lane & 3, r = lane >> 2, mi = lane >> 3, lr = lane & 7;
    const int cta = blockIdx.x, fin = cta - kFirstFinisher;
    uint32_t* box = mailbox(cta);
    const uint32_t full = sm + kOffBar;
    const float xin = fin >= 0 ? __bfloat162float(x[16 * fin + (lane & 15) / 2 + 8 * (lane & 1)]) : 0.f;
    uint32_t* hid_dst = hidden(10 * j + t / 24) + 48 * h + 2 * (t % 24);

    if (t < 144) put4(mailbox(cta ^ (t / 48 + 1)) + 4 * t, 0, 0, 0, 0);
    if (t < 96) put4(mailbox(cta ^ (t / 24)) + kBoxFfn + 4 * t, 0, 0, 0, 0);
    else if (t < 104) put4(mailbox(cta ^ ((t - 96) / 2)) + kBoxStat + 4 * (t - 96), 0, 0, 0, 0);
    else if (t >= 280) {
        uint32_t* words = box_pair(kCtas + 10 * j + (t - 280) / 4) + h * 16 + 4 * (t & 3);
        put4(words, 0, 0, 0, 0);
        put4(words + kCopy, 0, 0, 0, 0);
    }
    if (t < 240) put2(hid_dst, 0, 0);
    __syncwarp();
    bar_sync<kBarInit, 480>();

    if (w >= 6 && (w < 8 || fin >= 0)) {
        __nanosleep(2000);
        const uint32_t trip = round_trips(box_pair(w < 8 ? cta : kCtas + fin) + (w & 1) * kCopy + kTripLine, lane);
        if (lane == 0) asm volatile("st.volatile.shared.u32 [%0], %1;" :: "r"(sm + kOffTrip + 4 * (w - 6)), "r"(trip) : "memory");
        __syncwarp();
    }
    if (w < 3) {
        bar_sync<kBarStat, 160>();
        uint32_t s[4];
        gather([&](int i) { return box + kBoxFfn + 96 * i + t; }, s, ~0u, 200);
        const float sum = bf16r((untagged(s[0]) + untagged(s[1])) + (untagged(s[2]) + untagged(s[3])));
        const float up = __shfl_down_sync(~0u, sum, 1);
        if (!(lane & 1))
            reinterpret_cast<uint32_t*>(smem + kOffSend)[16 * w + r + 4 * (lane & 2)] = tagged(bf16r(bf16r(silu(sum)) * up));
    } else if (w == 9) {
        bar_sync<kBarStat, 160>();
        uint64_t st[1] = {0};
        if (lane < 4) gather([&](int) { return box + kBoxStat + 8 * lane; }, st, 15u, 200);
        __syncwarp();
        const float m = untagged((uint32_t)st[0]), l = untagged((uint32_t)(st[0] >> 32));
        float gm = fmaxf(m, __shfl_xor_sync(~0u, m, 1));
        gm = fmaxf(gm, __shfl_xor_sync(~0u, gm, 2));
        const float e = __expf(m - gm);
        float den = e * l;
        den += __shfl_xor_sync(~0u, den, 1);
        den += __shfl_xor_sync(~0u, den, 2);
        if (lane == 0) reinterpret_cast<float*>(smem + kOffRed)[8] = __fdividef(e, den);
        const uint32_t side = ((uint32_t)(st[0] >> 32) & 1) * kCopy;
        if (lane < 4) reinterpret_cast<uint32_t*>(smem + kOffSide)[lane] = side;
#pragma unroll
        for (int i = 1; i < 4; i++) {
            uint32_t* words = box_pair(cta ^ i) + __shfl_sync(~0u, side, i) + 192 * (i - 1) + 4 * lane;
            put4(words, 0, 0, 0, 0);
            if (lane < 16) put4(words + 128, 0, 0, 0, 0);
        }
        __syncwarp();
        bar_arrive<kBarScale, 160>();
    }
    __syncwarp();
    bar_sync<kBarProj, 320>();
    if (t < 240) {
        const uint2 v = *reinterpret_cast<const uint2*>(smem + kOffSend + 8 * (t % 24));
        put2(hid_dst, v.x, v.y);
    }
    __syncwarp();
    if (fin >= 0) {
        if (w < 8) {
            __nanosleep(4000);
            uint64_t v[3];
            gather([&](int i) { return hidden(fin) + 2 * (t + 256 * i); }, v, ~0u, 200);
    #pragma unroll
            for (int i = 0; i < 3; i++) {
                const int pair = t + 256 * i;
                const int off = (pair >> 4) * 64 + (pair & 3) * 16 + ((pair >> 3) & 1) * 8 + ((pair >> 2) & 1) * 4;
                *reinterpret_cast<uint32_t*>(smem + kOffHid + off) = __byte_perm((uint32_t)v[i], (uint32_t)(v[i] >> 32), 0x7632);
            }
        }
        bar_sync<kBarProj, 320>();
    }

    const uint32_t lin = ((mi >> 1) * 8 + lr) * 320 + (2 * w + (mi & 1)) * 16;
    constexpr int kSlotWo = kLdWo % kStages, kSlotDown = kLdDown % kStages;
    static_assert(kLdWo / kStages == (kLoads - 1) / kStages, "the last loads share a phase");
    constexpr uint32_t parity = (kLdWo / kStages) & 1;
    uint32_t wo = sm + kSlotWo * kStageBytes + (lin ^ (((lin >> 7) & 3) << 4));
    uint32_t lead = lane < 4, bv = sm + kOffQ + lane * 16;
    uint32_t* dst = box_pair(kCtas + 10 * j + w) + h * 16 + 2 * r;
    pin(wo); pin(lead); pin(bv); pin(dst);

#pragma unroll 1
    for (uint32_t pass = 0; pass < 2; pass++) {
        uint32_t writer = pass && quad == 0;
        pin(writer);
        if (pass) bar_sync<kBarGate, 448>();
        uint32_t tag;
        asm volatile("ld.volatile.shared.u32 %0, [%1];" : "=r"(tag) : "r"(sm + kOffTag) : "memory");
        uint32_t a[3][4][4];
        auto fetch = [&](int k) {
#pragma unroll
            for (int i = 0; i < 4; i++) ldsm4t(a[k][i], wo + k * kStageBytes + i * (16 * 320));
        };
        if (pass) mbar_wait(full + 8 * kSlotWo, parity);
        fetch(0);
        float c[4][4];
#pragma unroll
        for (int k = 0; k < 4; k++) c[k][0] = c[k][1] = c[k][2] = c[k][3] = 0.f;
        uint4 b[6];
#pragma unroll
        for (int k = 0; k < 6; k++) b[k] = make_uint4(0, 0, 0, 0);

        bool have1 = false, have2 = false;
        for (unsigned n = 0; !mbar_test(sm + kOffVecBar, 0) && pass; n++) {
            if (!have1 && mbar_test(full + 8 * (kSlotWo + 1), parity)) {
                fetch(1);
                have1 = true;
            }
            if (!have2 && mbar_test(full + 8 * (kSlotWo + 2), parity)) {
                fetch(2);
                have2 = true;
            }
            if (n > kSpinLimit) __trap();
        }
#pragma unroll
        for (int k = 0; k < 6; k++) lds128_if(b[k], bv + 128 * k, lead);
#pragma unroll
        for (int k = 0; k < 2; k++) {
            if (k == 1 && !have1) {
                for (unsigned n = 0; !mbar_test(full + 8 * (kSlotWo + 1), parity) && pass; n++) if (n > kSpinLimit) __trap();
                fetch(1);
            }
            mma(c[0], a[k][0], b[2 * k].x, b[2 * k].y);
            mma(c[1], a[k][1], b[2 * k].z, b[2 * k].w);
            mma(c[2], a[k][2], b[2 * k + 1].x, b[2 * k + 1].y);
            mma(c[3], a[k][3], b[2 * k + 1].z, b[2 * k + 1].w);
        }
        if (!have2) {
            for (unsigned n = 0; !mbar_test(full + 8 * (kSlotWo + 2), parity) && pass; n++) if (n > kSpinLimit) __trap();
            fetch(2);
        }
        mma(c[0], a[2][0], b[4].x, b[4].y);
        mma(c[1], a[2][1], b[4].z, b[4].w);
        mma(c[2], a[2][2], b[5].x, b[5].y);
        mma(c[3], a[2][3], b[5].z, b[5].w);
        const uint32_t s0 = (__float_as_uint((c[0][0] + c[1][0]) + (c[2][0] + c[3][0])) & ~3u) | tag;
        const uint32_t s1 = (__float_as_uint((c[0][2] + c[1][2]) + (c[2][2] + c[3][2])) & ~3u) | tag;
        put2_if(dst, s0, s1, writer);
        put2_if(dst + kCopy, s0, s1, writer);
        if (fin < 0) continue;

        if (w < 8) {
            const uint32_t dl = ((mi >> 1) * 8 + lr) * 32 + (mi & 1) * 16;
            uint32_t tile = sm + kSlotDown * kStageBytes + w * (96 * 32) + (dl ^ (((dl >> 7) & 1) << 4));
            uint32_t part = sm + kOffPart + r * 32 + w * 4;
            pin(tile); pin(part);
#pragma unroll
            for (int k = 0; k < 6; k++) lds128_if(b[k], sm + kOffHid + (24 * (k / 3) + 3 * w + k % 3) * 64 + lane * 16, lead);
#pragma unroll
            for (int k = 0; k < 3; k++) c[k][0] = c[k][1] = c[k][2] = c[k][3] = 0.f;
#pragma unroll
            for (int k = 0; k < 2; k++) {
                for (unsigned n = 0; !mbar_test(full + 8 * (kSlotDown + k), parity) && pass; n++) if (n > kSpinLimit) __trap();
                uint32_t f[6][4];
#pragma unroll
                for (int i = 0; i < 6; i++) ldsm4t(f[i], tile + k * kStageBytes + i * 512);
#pragma unroll
                for (int i = 0; i < 3; i++) mma(c[i], f[2 * i], b[3 * k + i].x, b[3 * k + i].y);
#pragma unroll
                for (int i = 0; i < 3; i++) mma(c[i], f[2 * i + 1], b[3 * k + i].z, b[3 * k + i].w);
            }
            asm volatile("{\n.reg .pred p;\nsetp.eq.u32 p, %3, 0;\n@p st.shared.f32 [%0], %1;\n@p st.shared.f32 [%0 + 256], %2;\n}"
                         :: "r"(part), "f"(c[0][0] + c[1][0] + c[2][0]), "f"(c[0][2] + c[1][2] + c[2][2]), "r"(quad) : "memory");
            __syncwarp();
            if (lane == 0) mbar_arrive(sm + kOffPartBar);
        } else if (w == 9) {
            const int col = (lane & 15) / 2 + 8 * (lane & 1);
            const uint4 trip = lds128(sm + kOffTrip);
            uint32_t* src = box_pair(kCtas + fin) + (trip.w < trip.z ? kCopy : 0) + lane;
            __nv_bfloat16* res = (pass ? out + 16 * fin : reinterpret_cast<__nv_bfloat16*>(g_sink)) + col;
            uint32_t part = sm + kOffPart + col * 32;
            pin(src); pin(res); pin(part);
            auto gate = [&]() {
                const uint4 p0 = lds128(part), p1 = lds128(part + 16);
                const float d = ((__uint_as_float(p0.x) + __uint_as_float(p0.y)) + (__uint_as_float(p0.z) + __uint_as_float(p0.w))) +
                                ((__uint_as_float(p1.x) + __uint_as_float(p1.y)) + (__uint_as_float(p1.z) + __uint_as_float(p1.w)));
                return bf16r(silu(bf16r(d)));
            };
            uint32_t v[16];
#pragma unroll
            for (int i = 0; i < 16; i++) v[i] = pass ^ 1;
            if (!pass) tag = 1;
            float g = 0.f;
            bool have_g = false;
            for (unsigned n = 0; !mbar_test(full + 8 * kSlotDown, parity) && pass; n++) if (n > kSpinLimit) __trap();
            const uint32_t start = clock_lo();
            for (unsigned n = 0;; n++) {
#pragma unroll
                for (int i = 0; i < 16; i++) peek(src + 32 * i, v[i], tag);
                if (!have_g && (mbar_test(sm + kOffPartBar, pass) || !pass)) {
                    g = gate();
                    have_g = pass;
                }
                uint32_t have = ~(uint32_t)((int)(clock_lo() - start) >> 31);
#pragma unroll
                for (int i = 0; i < 16; i++) have &= v[i];
                pin(have);
                if (__all_sync(~0u, have & tag)) break;
                if (n > kSpinLimit) __trap();
            }
            float sum[8];
#pragma unroll
            for (int i = 0; i < 8; i++) sum[i] = __uint_as_float(v[i]) + __uint_as_float(v[i + 8]);
            float s = ((sum[0] + sum[1]) + (sum[2] + sum[3])) + ((sum[4] + sum[5]) + (sum[6] + sum[7]));
            s = bf16r(s + __shfl_xor_sync(~0u, s, 16));
            if (!have_g) {
                for (unsigned n = 0; !mbar_test(sm + kOffPartBar, pass); n++) if (n > kSpinLimit) __trap();
                g = gate();
            }
            *res = __float2bfloat16_rn(xin + bf16r(s * g));
        }
    }
}

__global__ void __launch_bounds__(kThreads, 1)
decode_block_kernel(const uint8_t* __restrict__ wq_bytes, const __nv_bfloat16* __restrict__ x, __nv_bfloat16* __restrict__ out,
                    const __grid_constant__ Maps maps) {
    if (threadIdx.x < 4 * 48) {
        constexpr int kPitch = kH * kDh * 2;
        const uint8_t* line = wq_bytes + ((160 * (blockIdx.x & 3) * kPitch + (blockIdx.x >> 2) * (kDh * 2)) +
                                          (threadIdx.x >> 2) * kPitch + (threadIdx.x & 3) * 128);
        asm volatile("prefetch.global.L2 [%0];" :: "l"(line) : "memory");
    }
    extern __shared__ __align__(1024) uint8_t smem[];
    const uint32_t sm = (uint32_t)__cvta_generic_to_shared(smem);
    const int w = threadIdx.x >> 5;
    const int h = blockIdx.x >> 2, j = blockIdx.x & 3;
    uint64_t pol;
    asm volatile("createpolicy.fractional.L2::evict_first.b64 %0, 1.0;" : "=l"(pol));
    uint32_t sm0 = sm;
    const CUtensorMap* wq = &maps.wq;
    pin(sm0);
    pin(wq);
    if (threadIdx.x == 128) {
        first_loads(wq, sm0, h, j, pol);
#pragma unroll
        for (int i = 0; i < kStages; i++) {
            if (i >= kLdGate) mbar_init(sm + kOffBar + 8 * i, 1);
            mbar_init(sm + kOffBar + 8 * (kStages + i), 5);
        }
        mbar_init(sm + kOffVecBar, 4);
        mbar_init(sm + kOffPartBar, 8);
        asm volatile("fence.mbarrier_init.release.cluster;" ::: "memory");
    }
    __syncwarp();
    if (w == 4) {
        bar_arrive<kBarMonitor, 64>();
        bar_arrive<kBarInit, 480>();
        if (threadIdx.x == 128) producer(maps, sm, h, j, pol);
    } else if (w == 5) {
        bar_sync<kBarMonitor, 64>();
        if (threadIdx.x == 160) monitor(sm, h);
    } else if (w < 4) {
        consumer(x, smem, sm, j);
    } else {
        projector(x, out, smem, sm, h, j);
    }
}

typedef CUresult (*EncodeFn)(CUtensorMap*, CUtensorMapDataType, cuuint32_t, void*, const cuuint64_t*, const cuuint64_t*,
                             const cuuint32_t*, const cuuint32_t*, CUtensorMapInterleave, CUtensorMapSwizzle,
                             CUtensorMapL2promotion, CUtensorMapFloatOOBfill);

void encode3(EncodeFn enc, CUtensorMap* tm, const void* p, uint64_t rows, uint64_t cols, uint32_t inner, uint32_t segs,
             uint32_t box_rows, CUtensorMapSwizzle sw,
             CUtensorMapL2promotion promo = CU_TENSOR_MAP_L2_PROMOTION_NONE) {
    const cuuint64_t dims[3] = {inner, cols / inner, rows};
    const cuuint64_t strides[2] = {inner * 2ull, cols * 2ull};
    const cuuint32_t box[3] = {inner, segs, box_rows};
    const cuuint32_t es[3] = {1, 1, 1};
    enc(tm, CU_TENSOR_MAP_DATA_TYPE_BFLOAT16, 3, const_cast<void*>(p), dims, strides, box, es,
        CU_TENSOR_MAP_INTERLEAVE_NONE, sw, promo, CU_TENSOR_MAP_FLOAT_OOB_FILL_NONE);
}

}

extern "C" void kernel_launch(void* const* d_in, const int* in_sizes, int n_in, void* d_out, int out_size) {
    (void)in_sizes; (void)n_in; (void)out_size;
    static EncodeFn enc = nullptr;
    if (!enc) {
        void* fn = nullptr;
        cudaDriverEntryPointQueryResult qr;
        cudaGetDriverEntryPoint("cuTensorMapEncodeTiled", &fn, cudaEnableDefault, &qr);
        enc = (EncodeFn)fn;
        cudaFuncSetAttribute(decode_block_kernel, cudaFuncAttributeMaxDynamicSharedMemorySize, kSmemBytes);
    }
    Maps maps;
    encode3(enc, &maps.k, d_in[1], (uint64_t)kH * kSk, kDh, 64, 3, 64, CU_TENSOR_MAP_SWIZZLE_128B);
    encode3(enc, &maps.v, d_in[2], (uint64_t)kH * kSk, kDh, 64, 3, 64, CU_TENSOR_MAP_SWIZZLE_128B);
    encode3(enc, &maps.wq, d_in[3], kD, kH * kDh, 64, 3, 64, CU_TENSOR_MAP_SWIZZLE_128B);
    encode3(enc, &maps.wq_tail, d_in[3], kD, kH * kDh, 64, 3, 32, CU_TENSOR_MAP_SWIZZLE_128B);
    encode3(enc, &maps.wo, d_in[4], kH * kDh, kD, 32, 5, 64, CU_TENSOR_MAP_SWIZZLE_64B);
    encode3(enc, &maps.gate, d_in[6], kD, kF, 48, 1, 160, CU_TENSOR_MAP_SWIZZLE_NONE);
    encode3(enc, &maps.up, d_in[7], kD, kF, 48, 1, 160, CU_TENSOR_MAP_SWIZZLE_NONE);
    encode3(enc, &maps.down, d_in[8], kF, kD, 16, 1, 256, CU_TENSOR_MAP_SWIZZLE_32B, CU_TENSOR_MAP_L2_PROMOTION_L2_256B);
    decode_block_kernel<<<kCtas, kThreads, kSmemBytes>>>(
        (const uint8_t*)d_in[3], (const __nv_bfloat16*)d_in[0], (__nv_bfloat16*)d_out, maps);
}
```

```cpp
#include <cuda_runtime.h>
#include <cuda_bf16.h>
#include <cuda.h>
#include <stdint.h>

namespace {

constexpr int kH = 32, kSk = 4096, kDh = 192, kD = 640, kF = 1536;
constexpr int kCtas = 128, kThreads = 512;
constexpr int kFinishers = kD / 16, kFirstFinisher = kCtas - kFinishers;
constexpr int kStageBytes = 24576, kStages = 9;
constexpr int kTiles = 16;
constexpr int kLdGate = 3, kLdK = 5, kLdV = kLdK + kTiles, kLdWo = kLdV + kTiles;
constexpr int kLdDown = kLdWo + 3, kLoads = kLdDown + 2;

__host__ __device__ constexpr int load_bytes(int i) {
    return i == 2 ? kStageBytes / 2 : i >= kLdGate && i < kLdK ? 160 * 96 : i >= kLdWo && i < kLdDown ? 64 * 320 : kStageBytes;
}
__device__ __forceinline__ int gate_tile(int h) { return 2 * (h >> 2) + 1; }

constexpr int kUnit = 512, kWindow = 176, kWindowEnd = 120, kStagger = 192, kFinisherLead = 2560;
constexpr int kLdPaced = 8, kDepth = 3;
__host__ __device__ constexpr int units_through(int i) {
    int sum = 0;
    for (int k = 0; k <= i; k++) sum += load_bytes(k) / kUnit;
    return sum;
}
constexpr int kLaunchUnits = 1 << 18;
constexpr int kPadUnits = kLaunchUnits - kCtas * units_through(kLdDown - 1) - kFinishers * 2 * (kStageBytes / kUnit);
static_assert(kPadUnits >= 0, "padding");

constexpr int kOffScore = kStages * kStageBytes;
constexpr int kOffP = kOffScore + 4096;
constexpr int kOffXn = kOffP + 4096;
constexpr int kOffQ = kOffXn + 640;
constexpr int kOffSend = kOffQ + 768;
constexpr int kOffRed = kOffSend + 192;
constexpr int kOffTag = kOffRed + 44;
constexpr int kOffSide = kOffTag + 4;
constexpr int kOffTrip = kOffSide + 16;
constexpr int kOffBar = kOffTrip + 16;
constexpr int kOffVecBar = kOffBar + 16 * kStages;
constexpr int kOffPartBar = kOffVecBar + 8;
constexpr int kSmemBytes = kOffPartBar + 8;
constexpr int kOffHid = kOffScore;
constexpr int kOffPart = kOffHid + 2 * kF;
constexpr int kOffGate = kOffPart + 512;

constexpr int kBoxFfn = 576, kBoxStat = 960, kBoxWords = 1024;
constexpr int kCopy = 1024, kTripLine = 640;
constexpr int kAtLanded = kCtas + kFinishers, kAtBox = kAtLanded + 1, kAtHid = kAtBox + kCtas * kBoxWords / (2 * kCopy);
constexpr unsigned kSpinLimit = 1u << 24;

constexpr int kBarMain = 1, kBarInit = 2, kBarMonitor = 3, kBarStat = 4, kBarGate = 5, kBarScale = 6, kBarProj = 7;

struct Maps { CUtensorMap wq, wq_tail, gate, up, k, v, down, wo; };

__device__ __align__(128) uint32_t g_pairs[(kAtHid + kFinishers + 1) * 2 * kCopy];
__device__ __align__(128) uint32_t g_sink[8];

__device__ __forceinline__ uint32_t* box_pair(int i) {
    constexpr uintptr_t kMask = 8 * kCopy - 1;
    return reinterpret_cast<uint32_t*>((reinterpret_cast<uintptr_t>(g_pairs) + kMask) & ~kMask) + i * (2 * kCopy);
}
__device__ __forceinline__ uint32_t* landed_units() { return box_pair(kAtLanded) + kCopy; }
__device__ __forceinline__ uint32_t* mailbox(int cta) { return box_pair(kAtBox) + cta * kBoxWords; }
__device__ __forceinline__ uint32_t* hidden(int fin) { return box_pair(kAtHid + fin); }

__device__ __forceinline__ void mbar_init(uint32_t bar, uint32_t cnt) {
    asm volatile("mbarrier.init.shared::cta.b64 [%0], %1;" :: "r"(bar), "r"(cnt) : "memory");
}
__device__ __forceinline__ void mbar_expect_tx(uint32_t bar, uint32_t bytes) {
    asm volatile("mbarrier.arrive.expect_tx.shared::cta.b64 _, [%0], %1;" :: "r"(bar), "r"(bytes) : "memory");
}
__device__ __forceinline__ void mbar_arrive(uint32_t bar) {
    asm volatile("mbarrier.arrive.shared::cta.b64 _, [%0];" :: "r"(bar) : "memory");
}
__device__ __forceinline__ bool mbar_try(uint32_t bar, uint32_t parity) {
    uint32_t ok;
    asm volatile("{\n.reg .pred p;\nmbarrier.try_wait.parity.shared::cta.b64 p, [%1], %2;\nselp.u32 %0, 1, 0, p;\n}"
                 : "=r"(ok) : "r"(bar), "r"(parity) : "memory");
    return ok;
}
__device__ __forceinline__ bool mbar_test(uint32_t bar, uint32_t parity) {
    uint32_t ok;
    asm volatile("{\n.reg .pred p;\nmbarrier.test_wait.parity.shared::cta.b64 p, [%1], %2;\nselp.u32 %0, 1, 0, p;\n}"
                 : "=r"(ok) : "r"(bar), "r"(parity) : "memory");
    return ok;
}
__device__ __forceinline__ void mbar_wait(uint32_t bar, uint32_t parity) {
    unsigned n = 0;
    while (!mbar_try(bar, parity)) { if (++n > kSpinLimit) __trap(); }
}
__device__ __forceinline__ void tma3(uint32_t dst, const CUtensorMap* tm, int c0, int c1, int c2, uint32_t bar, uint64_t pol) {
    asm volatile("cp.async.bulk.tensor.3d.shared::cluster.global.mbarrier::complete_tx::bytes.L2::cache_hint"
                 " [%0], [%1, {%3, %4, %5}], [%2], %6;"
                 :: "r"(dst), "l"(tm), "r"(bar), "r"(c0), "r"(c1), "r"(c2), "l"(pol) : "memory");
}
__device__ __forceinline__ void ldsm4(uint32_t (&a)[4], uint32_t addr) {
    asm volatile("ldmatrix.sync.aligned.m8n8.x4.shared.b16 {%0,%1,%2,%3}, [%4];"
                 : "=r"(a[0]), "=r"(a[1]), "=r"(a[2]), "=r"(a[3]) : "r"(addr) : "memory");
}
__device__ __forceinline__ void ldsm4t(uint32_t (&a)[4], uint32_t addr) {
    asm volatile("ldmatrix.sync.aligned.m8n8.x4.trans.shared.b16 {%0,%1,%2,%3}, [%4];"
                 : "=r"(a[0]), "=r"(a[1]), "=r"(a[2]), "=r"(a[3]) : "r"(addr) : "memory");
}
__device__ __forceinline__ void mma(float (&c)[4], const uint32_t (&a)[4], uint32_t b0, uint32_t b1) {
    asm("mma.sync.aligned.m16n8k16.row.col.f32.bf16.bf16.f32 {%0,%1,%2,%3}, {%4,%5,%6,%7}, {%8,%9}, {%0,%1,%2,%3};"
                 : "+f"(c[0]), "+f"(c[1]), "+f"(c[2]), "+f"(c[3])
                 : "r"(a[0]), "r"(a[1]), "r"(a[2]), "r"(a[3]), "r"(b0), "r"(b1));
}
__device__ __forceinline__ uint4 lds128(uint32_t addr) {
    uint4 v;
    asm volatile("ld.shared.v4.u32 {%0,%1,%2,%3}, [%4];" : "=r"(v.x), "=r"(v.y), "=r"(v.z), "=r"(v.w) : "r"(addr) : "memory");
    return v;
}
__device__ __forceinline__ void lds128_if(uint4& v, uint32_t addr, uint32_t p) {
    asm volatile("{\n.reg .pred p;\nsetp.ne.u32 p, %5, 0;\n@p ld.shared.v4.u32 {%0,%1,%2,%3}, [%4];\n}"
                 : "+r"(v.x), "+r"(v.y), "+r"(v.z), "+r"(v.w) : "r"(addr), "r"(p) : "memory");
}
__device__ __forceinline__ void pin(uint32_t& v) { asm volatile("" : "+r"(v)); }
__device__ __forceinline__ void pin(float& v) { asm volatile("" : "+f"(v)); }
template <typename T> __device__ __forceinline__ void pin(T*& p) { asm volatile("" : "+l"(p)); }
template <int kId, int kCount> __device__ __forceinline__ void bar_sync() {
    asm volatile("bar.sync %0, %1;" :: "n"(kId), "n"(kCount) : "memory");
}
template <int kId, int kCount> __device__ __forceinline__ void bar_arrive() {
    asm volatile("bar.arrive %0, %1;" :: "n"(kId), "n"(kCount) : "memory");
}

__device__ __forceinline__ uint32_t tagged(float v) { return __float_as_uint(v) | 1u; }
__device__ __forceinline__ float untagged(uint32_t w) { return __uint_as_float(w & ~1u); }
__device__ __forceinline__ void put2(uint32_t* p, uint32_t a, uint32_t b) {
    asm volatile("st.relaxed.gpu.global.b64 [%0], %1;" :: "l"(p), "l"(((uint64_t)b << 32) | a) : "memory");
}
__device__ __forceinline__ void put2_if(uint32_t* p, uint32_t a, uint32_t b, uint32_t pred) {
    asm volatile("{\n.reg .pred p;\nsetp.ne.u32 p, %2, 0;\n@p st.relaxed.gpu.global.b64 [%0], %1;\n}"
                 :: "l"(p), "l"(((uint64_t)b << 32) | a), "r"(pred) : "memory");
}
__device__ __forceinline__ void put4(uint32_t* p, uint32_t a, uint32_t b, uint32_t c, uint32_t d) {
    asm volatile("st.relaxed.gpu.global.v4.b32 [%0], {%1, %2, %3, %4};" :: "l"(p), "r"(a), "r"(b), "r"(c), "r"(d) : "memory");
}
__device__ __forceinline__ void take(uint32_t* p, uint32_t& w) {
    asm volatile("atom.relaxed.gpu.global.exch.b32 %0, [%1], 0;" : "=r"(w) : "l"(p) : "memory");
}
__device__ __forceinline__ void take(uint32_t* p, uint64_t& w) {
    asm volatile("atom.relaxed.gpu.global.exch.b64 %0, [%1], 0;" : "=l"(w) : "l"(p) : "memory");
}
template <typename Word, int kN, typename Addr>
__device__ __forceinline__ void gather(Addr addr, Word (&w)[kN], unsigned mask, unsigned sleep_ns) {
#pragma unroll
    for (int i = 0; i < kN; i++) w[i] = 0;
    for (unsigned n = 0;; n++) {
        Word t[kN];
#pragma unroll
        for (int i = 0; i < kN; i++) take(addr(i), t[i]);
        uint32_t have = ~0u;
#pragma unroll
        for (int i = 0; i < kN; i++) {
            w[i] |= t[i];
            have &= (uint32_t)w[i];
        }
        pin(have);
        if (__all_sync(mask, have & 1)) break;
        if (n > kSpinLimit) __trap();
        if (sleep_ns) __nanosleep(sleep_ns);
    }
}
__device__ __forceinline__ void peek(const uint32_t* p, uint32_t& w, uint32_t tag) {
    asm volatile("{\n.reg .pred p;\n.reg .b32 t;\n"
                 "and.b32 t, %0, %2;\nsetp.eq.u32 p, t, 0;\n"
                 "@p ld.relaxed.gpu.global.b32 %0, [%1];\n}"
                 : "+r"(w) : "l"(p), "r"(tag) : "memory");
}
__device__ __forceinline__ uint32_t clock_lo() {
    uint32_t c;
    asm volatile("mov.u32 %0, %%clock;" : "=r"(c) :: "memory");
    return c;
}
__device__ __forceinline__ void spin(uint32_t cycles) {
    const uint32_t start = clock_lo();
    while (clock_lo() - start < cycles) {}
}
__device__ __forceinline__ uint32_t round_trips(uint32_t* line, int lane) {
    if (lane < 8) put4(line + 4 * lane, 0, 0, 0, 0);
    __syncwarp();
    uint32_t sum = 0, zero = 0;
#pragma unroll 1
    for (int i = 0; i < 4; i++) {
        const uint32_t start = clock_lo();
        uint32_t end;
        asm volatile("ld.relaxed.gpu.global.b32 %0, [%1];" : "=r"(end) : "l"(line + zero) : "memory");
        asm volatile("{\n.reg .pred p;\nsetp.ne.u32 p, %0, 0;\n@p trap;\nmov.u32 %0, %%clock;\n}" : "+r"(end) :: "memory");
        zero = (end - start) >> 31;
        if (i) sum += end - start;
    }
    return sum;
}

__device__ __forceinline__ float bf16r(float v) { return __bfloat162float(__float2bfloat16_rn(v)); }
__device__ __forceinline__ float bf_lo(uint32_t u) { return __uint_as_float(u << 16); }
__device__ __forceinline__ float bf_hi(uint32_t u) { return __uint_as_float(u & 0xffff0000u); }
__device__ __forceinline__ uint32_t pack_bf16(float lo, float hi) {
    __nv_bfloat162 t = __floats2bfloat162_rn(lo, hi);
    return *reinterpret_cast<uint32_t*>(&t);
}
__device__ __forceinline__ float silu(float v) { return __fdividef(v, 1.0f + __expf(-v)); }
__device__ __forceinline__ float pick3(int s, float a, float b, float c) { return s == 0 ? a : (s == 1 ? b : c); }

__device__ __forceinline__ int bvec_off(int mt, int r) {
    return (mt >> 1) * 128 + (r >> 1) * 16 + (mt & 1) * 8 + (r & 1) * 2;
}

struct Ring {
    uint32_t full, empty;
    int slot; uint32_t phase;
    __device__ __forceinline__ uint32_t acquire(uint32_t ring) {
        mbar_wait(full + 8 * slot, phase);
        return ring + slot * kStageBytes;
    }
    __device__ __forceinline__ void release(int lane) {
        __syncwarp();
        if (lane == 0) mbar_arrive(empty + 8 * slot);
        skip();
    }
    __device__ __forceinline__ void skip() {
        if (++slot == kStages) { slot = 0; phase ^= 1; }
    }
};

__device__ __forceinline__ void gemv384(float (&acc)[3][4], uint32_t tile, const uint32_t (&off)[3], uint32_t bvec) {
    const uint4 b = lds128(bvec);
    uint32_t a[2][3][4];
#pragma unroll
    for (int ks = 0; ks < 2; ks++)
#pragma unroll
        for (int m = 0; m < 3; m++) ldsm4t(a[ks][m], tile + off[m] + ks * (16 * 384));
#pragma unroll
    for (int m = 0; m < 3; m++) mma(acc[m], a[0][m], b.x, b.y);
#pragma unroll
    for (int m = 0; m < 3; m++) mma(acc[m], a[1][m], b.z, b.w);
}

__device__ __forceinline__ void zero3(float (&acc)[3][4]) {
#pragma unroll
    for (int m = 0; m < 3; m++)
#pragma unroll
        for (int i = 0; i < 4; i++) acc[m][i] = 0.f;
}

__device__ __forceinline__ void first_loads(const CUtensorMap* wq, uint32_t sm, int h, int j, uint64_t pol) {
#pragma unroll
    for (int i = 0; i < kLdGate; i++) {
        const uint32_t bar = sm + kOffBar + 8 * i;
        mbar_init(bar, 1);
        asm volatile("fence.mbarrier_init.release.cluster;" ::: "memory");
        tma3(sm + i * kStageBytes, wq + (i == 2), 0, 3 * h, 160 * j + 64 * i, bar, pol);
        mbar_expect_tx(bar, load_bytes(i));
    }
}

__device__ __forceinline__ void producer(const Maps& maps, uint32_t sm, int h, int j, uint64_t pol) {
    const uint32_t full = sm + kOffBar, empty = full + 8 * kStages;
    const int kvrow = h * kSk + j * (kTiles * 64);
    int landed = 0, need = kCtas * (units_through(kLdGate - 1) - kWindow) - h * kStagger - (blockIdx.x >= kFirstFinisher ? kFinisherLead : 0);
    static_assert(kCtas * (units_through(kLdPaced) - kWindow) > kH * kStagger + kFinisherLead, "load kLdPaced reads the counter");
    unsigned total = 0;
    int slot = kLdGate; uint32_t phase = 1;
    const int gate = kLdGate + gate_tile(h);
    const int fin = blockIdx.x - kFirstFinisher, loads = fin >= 0 ? kLoads : kLdDown;
#pragma unroll 1
    for (int i = kLdGate; i < loads; i++) {
        const uint32_t bar = full + 8 * slot, dst = sm + slot * kStageBytes;
        const CUtensorMap* tm; int c1, c2; uint32_t bytes;
        if (i < gate)          { tm = &maps.k;    c1 = 0;     c2 = kvrow + 64 * (i - kLdGate);    bytes = kStageBytes; }
        else if (i < gate + 2) { tm = &maps.gate + (i - gate); c1 = h; c2 = 160 * j;              bytes = 160 * 96; }
        else if (i < kLdV)     { tm = &maps.k;    c1 = 0;     c2 = kvrow + 64 * (i - kLdK);       bytes = kStageBytes; }
        else if (i < kLdWo)    { tm = &maps.v;    c1 = 0;     c2 = kvrow + 64 * (i - kLdV);       bytes = kStageBytes; }
        else if (i < kLdDown)  { tm = &maps.wo;   c1 = 5 * j; c2 = kDh * h + 64 * (i - kLdWo);    bytes = 64 * 320; }
        else                   { tm = &maps.down; c1 = fin;   c2 = 768 * (i - kLdDown);           bytes = kStageBytes; }
        need += bytes * kCtas / kUnit;
        if (i >= kLdDown) need = kCtas * (units_through(kLdDown - 1) - kWindowEnd) - kFinisherLead;
        if (i == kLdWo) need += kCtas * (kWindow - kWindowEnd);
        if (i > kLdWo && i < kLdDown) need += (h - kH / 2) * (kStagger / 2);
        if (i >= kStages) mbar_wait(empty + 8 * slot, phase);
        if (i < kLdPaced) mbar_wait(full + 8 * (i - kDepth), 0);
        for (unsigned n = 0; landed < need && i >= kLdPaced; n++) {
            asm volatile("ld.relaxed.gpu.global.u32 %0, [%1];" : "=r"(total) : "l"(landed_units()) : "memory");
            landed = (int)(total & (kLaunchUnits - 1));
            if (n > kSpinLimit) __trap();
        }
        mbar_expect_tx(bar, bytes);
        tma3(dst, tm, 0, c1, c2, bar, pol);
        if (i == kLdPaced) asm volatile("st.shared.u32 [%0], %1;" :: "r"(sm + kOffTag), "r"(1 + total / kLaunchUnits % 2) : "memory");
        if (i >= kLdDown) {
            tma3(dst + 8192, tm, 0, c1, c2 + 256, bar, pol);
            tma3(dst + 16384, tm, 0, c1, c2 + 512, bar, pol);
        }
        if (++slot == kStages) { slot = 0; phase ^= 1; }
    }
    if (blockIdx.x == kCtas - 1)
        asm volatile("red.relaxed.gpu.global.add.u32 [%0], %1;" :: "l"(landed_units()), "r"(kPadUnits) : "memory");
}

__device__ __forceinline__ void monitor(uint32_t sm, int h) {
    const int gate = kLdGate + gate_tile(h);
    const uint32_t full = sm + kOffBar, empty = full + 8 * kStages;
    int slot = 0; uint32_t phase = 0;
    const int loads = blockIdx.x >= kFirstFinisher ? kLoads : kLdDown;
#pragma unroll 1
    for (int i = 0; i < loads; i++) {
        mbar_wait(full + 8 * slot, phase);
        const int k = i < kLdGate || i >= kLdV ? i : i == gate || i == gate + 1 ? kLdGate : kLdK;
        const int units = load_bytes(k) / kUnit;
        asm volatile("red.relaxed.gpu.global.add.u32 [%0], %1;" :: "l"(landed_units()), "r"(units) : "memory");
        mbar_arrive(empty + 8 * slot);
        if (++slot == kStages) { slot = 0; phase ^= 1; }
    }
}

__device__ __forceinline__ void layer_norm(const __nv_bfloat16* __restrict__ x, uint8_t* smem, int j) {
    const int tid = threadIdx.x, lane = tid & 31;
    const uint4* x4 = reinterpret_cast<const uint4*>(x);
    uint4 xv[3];
    xv[0] = __ldg(x4 + lane);
    xv[1] = __ldg(x4 + 32 + lane);
    xv[2] = lane < 16 ? __ldg(x4 + 64 + lane) : make_uint4(0, 0, 0, 0);
    uint32_t xs = 0;
    if (tid < 80) xs = __ldg(reinterpret_cast<const uint32_t*>(x) + j * 80 + tid);

    for (int i = tid; i < (kOffRed - kOffXn) / 16; i += 128)
        *reinterpret_cast<uint4*>(smem + kOffXn + i * 16) = make_uint4(0, 0, 0, 0);

    float sum = 0.f;
#pragma unroll
    for (int i = 0; i < 3; i++) {
        const uint32_t u[4] = {xv[i].x, xv[i].y, xv[i].z, xv[i].w};
#pragma unroll
        for (int k = 0; k < 4; k++) sum += bf_lo(u[k]) + bf_hi(u[k]);
    }
#pragma unroll
    for (int s = 16; s > 0; s >>= 1) sum += __shfl_xor_sync(~0u, sum, s);
    const float mean = sum * (1.0f / kD);
    float sq = 0.f;
#pragma unroll
    for (int i = 0; i < 3; i++) {
        const uint32_t u[4] = {xv[i].x, xv[i].y, xv[i].z, xv[i].w};
        if (i < 2 || lane < 16) {
#pragma unroll
            for (int k = 0; k < 4; k++) {
                const float a = bf_lo(u[k]) - mean, b = bf_hi(u[k]) - mean;
                sq += a * a + b * b;
            }
        }
    }
#pragma unroll
    for (int s = 16; s > 0; s >>= 1) sq += __shfl_xor_sync(~0u, sq, s);
    const float mean_b = bf16r(mean);
    const float den = bf16r(__fsqrt_rn(bf16r(bf16r(sq * (1.0f / kD)) + 1e-5f)));
    bar_sync<kBarMain, 128>();
    if (tid < 80) {
        const int k = 2 * tid;
        const float a = __fdividef(bf16r(bf_lo(xs) - mean_b), den), b = __fdividef(bf16r(bf_hi(xs) - mean_b), den);
        const int off = (k >> 5) * 128 + ((k & 7) >> 1) * 16 + ((k >> 4) & 1) * 8 + ((k >> 3) & 1) * 4;
        *reinterpret_cast<uint32_t*>(smem + kOffXn + off) = pack_bf16(a, b);
    }
}

__device__ __forceinline__ void gate_up(Ring& ring, uint32_t sm) {
    const int lane = threadIdx.x & 31, w = threadIdx.x >> 5;
    const int quad = lane & 3, r = lane >> 2, mi = lane >> 3, lr = lane & 7;
    const uint32_t bsel = (r & 1) * 64 + quad * 16;
    const uint32_t off = ((mi >> 1) * 8 + lr) * 96 + (2 * w + (mi & 1)) * 16;
    uint32_t g0 = 0, g1 = 0;
#pragma unroll 1
    for (int g = 0; g < 2; g++) {
        const uint32_t tile = ring.acquire(sm);
        if (w < 3) {
            float c[4] = {0.f, 0.f, 0.f, 0.f};
#pragma unroll
            for (int kb = 0; kb < 5; kb++) {
                const uint4 b = lds128(sm + kOffXn + kb * 128 + bsel);
                uint32_t a0[4], a1[4];
                ldsm4t(a0, tile + off + kb * (32 * 96));
                ldsm4t(a1, tile + off + kb * (32 * 96) + 16 * 96);
                mma(c, a0, b.x, b.y);
                mma(c, a1, b.z, b.w);
            }
            if (g == 0) { g0 = tagged(c[0]); g1 = tagged(c[2]); }
            else put4(mailbox(blockIdx.x ^ quad) + kBoxFfn + 96 * quad + 4 * (8 * w + r), g0, tagged(c[0]), g1, tagged(c[2]));
        }
        ring.release(lane);
    }
}

__device__ __forceinline__ float scores_softmax(Ring& ring, uint8_t* smem, uint32_t sm) {
    const int tid = threadIdx.x, lane = tid & 31, w = tid >> 5;
    const int quad = lane & 3, r = lane >> 2, mi = lane >> 3, lr = lane & 7;
    float* score = reinterpret_cast<float*>(smem + kOffScore);
    float* red = reinterpret_cast<float*>(smem + kOffRed);
    uint32_t qf[24];
#pragma unroll
    for (int kb = 0; kb < 6; kb++) {
        const uint4 b = lds128(sm + kOffQ + kb * 128 + quad * 16);
        qf[4 * kb] = b.x; qf[4 * kb + 1] = b.y; qf[4 * kb + 2] = b.z; qf[4 * kb + 3] = b.w;
    }
    const int row = 16 * w + (mi & 1) * 8 + lr;
    uint32_t offk[3];
#pragma unroll
    for (int seg = 0; seg < 3; seg++)
        offk[seg] = row * 384 + seg * 128 + (((mi >> 1) ^ ((3 * row + seg) & 7)) << 4);
    const float scale = 0.07216878364870323f;
    float mx = -INFINITY;
#pragma unroll 1
    for (int t = 0; t < kTiles; t++) {
        if (t == gate_tile(blockIdx.x >> 2)) gate_up(ring, sm);
        const uint32_t tile = ring.acquire(sm);
        float c0[4] = {0.f, 0.f, 0.f, 0.f}, c1[4] = {0.f, 0.f, 0.f, 0.f};
        uint32_t a[12][4];
#pragma unroll
        for (int ks = 0; ks < 12; ks++) ldsm4(a[ks], tile + (offk[ks >> 2] ^ ((ks & 3) << 5)));
#pragma unroll
        for (int ks = 0; ks < 12; ks += 2) {
            mma(c0, a[ks], qf[2 * ks], qf[2 * ks + 1]);
            mma(c1, a[ks + 1], qf[2 * ks + 2], qf[2 * ks + 3]);
        }
        ring.release(lane);
        const float s = bf16r(bf16r((quad & 1) ? c0[2] + c1[2] : c0[0] + c1[0]) * scale);
        mx = fmaxf(mx, s);
        if (quad < 2) score[t * 64 + 16 * w + quad * 8 + r] = s;
    }
#pragma unroll
    for (int s = 16; s > 0; s >>= 1) mx = fmaxf(mx, __shfl_xor_sync(~0u, mx, s));
    if (lane == 0) red[w] = mx;
    bar_sync<kBarMain, 128>();
    mx = fmaxf(fmaxf(red[0], red[1]), fmaxf(red[2], red[3]));

    float lsum = 0.f;
    const int blk = tid >> 2;
    uint32_t hi[4], lo[4];
#pragma unroll
    for (int i = 0; i < 4; i++) {
        const float2 s = *reinterpret_cast<const float2*>(score + blk * 32 + i * 8 + 2 * quad);
        const float e0 = __expf(s.x - mx), e1 = __expf(s.y - mx);
        lsum += e0 + e1;
        hi[i] = pack_bf16(e0, e1);
        lo[i] = pack_bf16(e0 - bf_lo(hi[i]), e1 - bf_hi(hi[i]));
    }
    *reinterpret_cast<uint4*>(smem + kOffP + blk * 128 + quad * 16) = make_uint4(hi[0], hi[1], hi[2], hi[3]);
    *reinterpret_cast<uint4*>(smem + kOffP + blk * 128 + 64 + quad * 16) = make_uint4(lo[0], lo[1], lo[2], lo[3]);
#pragma unroll
    for (int s = 16; s > 0; s >>= 1) lsum += __shfl_xor_sync(~0u, lsum, s);
    if (lane == 0) red[4 + w] = lsum;
    return mx;
}

__device__ __forceinline__ void consumer(const __nv_bfloat16* __restrict__ x, uint8_t* smem, uint32_t sm, int j) {
    const int tid = threadIdx.x, lane = tid & 31, w = tid >> 5;
    const int quad = lane & 3, r = lane >> 2, mi = lane >> 3, lr = lane & 7;
    const int cta = blockIdx.x;
    float* red = reinterpret_cast<float*>(smem + kOffRed);

    layer_norm(x, smem, j);
    bar_sync<kBarInit, 480>();

    Ring ring{sm + kOffBar, sm + kOffBar + 8 * kStages, 0, 0};
    const uint32_t bsel = (r & 1) * 64 + quad * 16;
    const int frow = (mi >> 1) * 8 + lr;
    uint32_t off384[3];
#pragma unroll
    for (int m = 0; m < 3; m++) {
        const int chunk = 2 * (3 * w + m) + (mi & 1), seg = chunk >> 3;
        off384[m] = frow * 384 + seg * 128 + (((chunk & 7) ^ ((3 * frow + seg) & 7)) << 4);
    }

#pragma unroll 1
    for (int pass = 0; pass < 2; pass++) {
        const int mt = 3 * w + quad, pitch = pass ? 2 * kCopy : kBoxWords;
        uint32_t* boxes = (pass ? box_pair(0) : mailbox(0)) + 16 * mt + 2 * r;
        uint32_t* send[3];
#pragma unroll
        for (int i = 0; i < 3; i++) {
            send[i] = boxes + (cta ^ (i + 1)) * pitch + 192 * i;
            pin(send[i]);
        }
        uint32_t* recv = boxes + cta * pitch;
        uint32_t vec = sm + kOffQ + bvec_off(mt, r);
        pin(recv);
        pin(vec);

        float acc[3][4];
        zero3(acc);
        const int halves = pass ? 2 * kTiles : 5;
        uint32_t bv = sm + (pass ? kOffP : kOffXn) + bsel;
#pragma unroll 1
        for (int t = 0; t < halves; t += 2) {
            const uint32_t tile = ring.acquire(sm);
            gemv384(acc, tile, off384, bv);
            if (t + 1 < halves) gemv384(acc, tile + 32 * 384, off384, bv + 128);
            ring.release(lane);
            bv += 256;
        }
        float f = 1.f;
        if (pass) {
            bar_arrive<kBarGate, 448>();
            bar_sync<kBarScale, 160>();
            f = red[8];
            const uint4 side = lds128(sm + kOffSide);
            recv += side.x; send[0] += side.y; send[1] += side.z; send[2] += side.w;
        }

        const uint32_t a = tagged(f * pick3(quad, acc[0][0] + acc[0][1], acc[1][0] + acc[1][1], acc[2][0] + acc[2][1]));
        const uint32_t b = tagged(f * pick3(quad, acc[0][2] + acc[0][3], acc[1][2] + acc[1][3], acc[2][2] + acc[2][3]));
        if (quad < 3) {
#pragma unroll
            for (int i = 0; i < 3; i++) put2(send[i], a, b);
        }
        __syncwarp();
        uint64_t v[3];
        v[0] = v[1] = v[2] = 0;
        if (!pass) __nanosleep(600);
        spin(1000);
        if (quad < 3) gather([&](int i) { return recv + 192 * i; }, v, 0x77777777u, pass ? 0 : 500);
        __syncwarp();
        const uint32_t s0 = pack_bf16((untagged(a) + untagged((uint32_t)v[0])) + (untagged((uint32_t)v[1]) + untagged((uint32_t)v[2])), 0.f);
        const uint32_t s1 = pack_bf16((untagged(b) + untagged((uint32_t)(v[0] >> 32))) +
                                      (untagged((uint32_t)(v[1] >> 32)) + untagged((uint32_t)(v[2] >> 32))), 0.f);
        asm volatile("{\n.reg .pred p;\nsetp.ne.u32 p, %3, 3;\n@p st.shared.u16 [%0], %1;\n@p st.shared.u16 [%0 + 4], %2;\n}"
                     :: "r"(vec), "h"((uint16_t)s0), "h"((uint16_t)s1), "r"(quad) : "memory");
        __syncwarp();
        if (pass && lane == 0) mbar_arrive(sm + kOffVecBar);
        if (pass) break;
        bar_sync<kBarMain, 128>();
        const float mx = scores_softmax(ring, smem, sm);
        bar_sync<kBarMain, 128>();
        if (w == 0) {
            uint32_t trip0, trip1;
            asm volatile("ld.volatile.shared.v2.u32 {%0, %1}, [%2];" : "=r"(trip0), "=r"(trip1) : "r"(sm + kOffTrip) : "memory");
            const uint32_t sum = tagged((red[4] + red[5]) + (red[6] + red[7])) ^ __shfl_sync(~0u, trip0 <= trip1, 0);
            if (tid < 4) put2(mailbox(cta ^ tid) + kBoxStat + 8 * tid, tagged(mx), sum);
            __syncwarp();
            bar_arrive<kBarStat, 160>();
        }
    }
}

__device__ __forceinline__ void projector(const __nv_bfloat16* __restrict__ x, __nv_bfloat16* __restrict__ out, uint8_t* smem,
                                          uint32_t sm, int h, int j) {
    const int t = threadIdx.x - 192, lane = t & 31, w = t >> 5;
    const int quad = lane & 3, r = lane >> 2, mi = lane >> 3, lr = lane & 7;
    const int cta = blockIdx.x, fin = cta - kFirstFinisher;
    uint32_t* box = mailbox(cta);
    const uint32_t full = sm + kOffBar;
    const float xin = fin >= 0 ? __bfloat162float(x[16 * fin + (lane & 15) / 2 + 8 * (lane & 1)]) : 0.f;
    uint32_t* hid_dst = hidden(10 * j + t / 24) + 48 * h + 2 * (t % 24);

    if (t < 144) put4(mailbox(cta ^ (t / 48 + 1)) + 4 * t, 0, 0, 0, 0);
    if (t < 96) put4(mailbox(cta ^ (t / 24)) + kBoxFfn + 4 * t, 0, 0, 0, 0);
    else if (t < 104) put4(mailbox(cta ^ ((t - 96) / 2)) + kBoxStat + 4 * (t - 96), 0, 0, 0, 0);
    else if (t >= 280) {
        uint32_t* words = box_pair(kCtas + 10 * j + (t - 280) / 4) + h * 16 + 4 * (t & 3);
        put4(words, 0, 0, 0, 0);
        put4(words + kCopy, 0, 0, 0, 0);
    }
    if (t < 240) put2(hid_dst, 0, 0);
    __syncwarp();
    bar_sync<kBarInit, 480>();

    if (w >= 6 && (w < 8 || fin >= 0)) {
        __nanosleep(2000);
        const uint32_t trip = round_trips(box_pair(w < 8 ? cta : kCtas + fin) + (w & 1) * kCopy + kTripLine, lane);
        if (lane == 0) asm volatile("st.volatile.shared.u32 [%0], %1;" :: "r"(sm + kOffTrip + 4 * (w - 6)), "r"(trip) : "memory");
        __syncwarp();
    }
    if (w < 3) {
        bar_sync<kBarStat, 160>();
        uint32_t s[4];
        gather([&](int i) { return box + kBoxFfn + 96 * i + t; }, s, ~0u, 200);
        const float sum = bf16r((untagged(s[0]) + untagged(s[1])) + (untagged(s[2]) + untagged(s[3])));
        const float up = __shfl_down_sync(~0u, sum, 1);
        if (!(lane & 1))
            reinterpret_cast<uint32_t*>(smem + kOffSend)[16 * w + r + 4 * (lane & 2)] = tagged(bf16r(bf16r(silu(sum)) * up));
    } else if (w == 9) {
        bar_sync<kBarStat, 160>();
        uint64_t st[1] = {0};
        if (lane < 4) gather([&](int) { return box + kBoxStat + 8 * lane; }, st, 15u, 200);
        __syncwarp();
        const float m = untagged((uint32_t)st[0]), l = untagged((uint32_t)(st[0] >> 32));
        float gm = fmaxf(m, __shfl_xor_sync(~0u, m, 1));
        gm = fmaxf(gm, __shfl_xor_sync(~0u, gm, 2));
        const float e = __expf(m - gm);
        float den = e * l;
        den += __shfl_xor_sync(~0u, den, 1);
        den += __shfl_xor_sync(~0u, den, 2);
        if (lane == 0) reinterpret_cast<float*>(smem + kOffRed)[8] = __fdividef(e, den);
        const uint32_t side = ((uint32_t)(st[0] >> 32) & 1) * kCopy;
        if (lane < 4) reinterpret_cast<uint32_t*>(smem + kOffSide)[lane] = side;
#pragma unroll
        for (int i = 1; i < 4; i++) {
            uint32_t* words = box_pair(cta ^ i) + __shfl_sync(~0u, side, i) + 192 * (i - 1) + 4 * lane;
            put4(words, 0, 0, 0, 0);
            if (lane < 16) put4(words + 128, 0, 0, 0, 0);
        }
        __syncwarp();
        bar_arrive<kBarScale, 160>();
    }
    __syncwarp();
    bar_sync<kBarProj, 320>();
    if (t < 240) {
        const uint2 v = *reinterpret_cast<const uint2*>(smem + kOffSend + 8 * (t % 24));
        put2(hid_dst, v.x, v.y);
    }
    __syncwarp();
    if (fin >= 0) {
        if (w < 8) {
            __nanosleep(4000);
            uint64_t v[3];
            gather([&](int i) { return hidden(fin) + 2 * (t + 256 * i); }, v, ~0u, 200);
    #pragma unroll
            for (int i = 0; i < 3; i++) {
                const int pair = t + 256 * i;
                const int off = (pair >> 4) * 64 + (pair & 3) * 16 + ((pair >> 3) & 1) * 8 + ((pair >> 2) & 1) * 4;
                *reinterpret_cast<uint32_t*>(smem + kOffHid + off) = __byte_perm((uint32_t)v[i], (uint32_t)(v[i] >> 32), 0x7632);
            }
        }
        bar_sync<kBarProj, 320>();
    }

    const uint32_t lin = ((mi >> 1) * 8 + lr) * 320 + (2 * w + (mi & 1)) * 16;
    constexpr int kSlotWo = kLdWo % kStages, kSlotDown = kLdDown % kStages;
    static_assert(kLdWo / kStages == (kLoads - 1) / kStages, "the last loads share a phase");
    constexpr uint32_t parity = (kLdWo / kStages) & 1;
    uint32_t wo = sm + kSlotWo * kStageBytes + (lin ^ (((lin >> 7) & 3) << 4));
    uint32_t lead = lane < 4, bv = sm + kOffQ + lane * 16;
    uint32_t* dst = box_pair(kCtas + 10 * j + w) + h * 16 + 2 * r;
    pin(wo); pin(lead); pin(bv); pin(dst);

#pragma unroll 1
    for (uint32_t pass = 0; pass < 2; pass++) {
        uint32_t writer = pass && quad == 0;
        pin(writer);
        if (pass) bar_sync<kBarGate, 448>();
        uint32_t tag;
        asm volatile("ld.volatile.shared.u32 %0, [%1];" : "=r"(tag) : "r"(sm + kOffTag) : "memory");
        uint32_t a[3][4][4];
        auto fetch = [&](int k) {
#pragma unroll
            for (int i = 0; i < 4; i++) ldsm4t(a[k][i], wo + k * kStageBytes + i * (16 * 320));
        };
        if (pass) mbar_wait(full + 8 * kSlotWo, parity);
        fetch(0);
        float c[4][4];
#pragma unroll
        for (int k = 0; k < 4; k++) c[k][0] = c[k][1] = c[k][2] = c[k][3] = 0.f;
        uint4 b[6];
#pragma unroll
        for (int k = 0; k < 6; k++) b[k] = make_uint4(0, 0, 0, 0);

        bool have1 = false, have2 = false;
        for (unsigned n = 0; !mbar_test(sm + kOffVecBar, 0) && pass; n++) {
            if (!have1 && mbar_test(full + 8 * (kSlotWo + 1), parity)) {
                fetch(1);
                have1 = true;
            }
            if (!have2 && mbar_test(full + 8 * (kSlotWo + 2), parity)) {
                fetch(2);
                have2 = true;
            }
            if (n > kSpinLimit) __trap();
        }
#pragma unroll
        for (int k = 0; k < 6; k++) lds128_if(b[k], bv + 128 * k, lead);
#pragma unroll
        for (int k = 0; k < 2; k++) {
            if (k == 1 && !have1) {
                for (unsigned n = 0; !mbar_test(full + 8 * (kSlotWo + 1), parity) && pass; n++) if (n > kSpinLimit) __trap();
                fetch(1);
            }
            mma(c[0], a[k][0], b[2 * k].x, b[2 * k].y);
            mma(c[1], a[k][1], b[2 * k].z, b[2 * k].w);
            mma(c[2], a[k][2], b[2 * k + 1].x, b[2 * k + 1].y);
            mma(c[3], a[k][3], b[2 * k + 1].z, b[2 * k + 1].w);
        }
        if (!have2) {
            for (unsigned n = 0; !mbar_test(full + 8 * (kSlotWo + 2), parity) && pass; n++) if (n > kSpinLimit) __trap();
            fetch(2);
        }
        mma(c[0], a[2][0], b[4].x, b[4].y);
        mma(c[1], a[2][1], b[4].z, b[4].w);
        mma(c[2], a[2][2], b[5].x, b[5].y);
        mma(c[3], a[2][3], b[5].z, b[5].w);
        const uint32_t s0 = (__float_as_uint((c[0][0] + c[1][0]) + (c[2][0] + c[3][0])) & ~3u) | tag;
        const uint32_t s1 = (__float_as_uint((c[0][2] + c[1][2]) + (c[2][2] + c[3][2])) & ~3u) | tag;
        put2_if(dst, s0, s1, writer);
        put2_if(dst + kCopy, s0, s1, writer);
        if (fin < 0) continue;

        if (w < 8) {
            const uint32_t dl = ((mi >> 1) * 8 + lr) * 32 + (mi & 1) * 16;
            uint32_t tile = sm + kSlotDown * kStageBytes + w * (96 * 32) + (dl ^ (((dl >> 7) & 1) << 4));
            uint32_t part = sm + kOffPart + r * 32 + w * 4;
            pin(tile); pin(part);
#pragma unroll
            for (int k = 0; k < 6; k++) lds128_if(b[k], sm + kOffHid + (24 * (k / 3) + 3 * w + k % 3) * 64 + lane * 16, lead);
#pragma unroll
            for (int k = 0; k < 3; k++) c[k][0] = c[k][1] = c[k][2] = c[k][3] = 0.f;
#pragma unroll
            for (int k = 0; k < 2; k++) {
                for (unsigned n = 0; !mbar_test(full + 8 * (kSlotDown + k), parity) && pass; n++) if (n > kSpinLimit) __trap();
                uint32_t f[6][4];
#pragma unroll
                for (int i = 0; i < 6; i++) ldsm4t(f[i], tile + k * kStageBytes + i * 512);
#pragma unroll
                for (int i = 0; i < 3; i++) mma(c[i], f[2 * i], b[3 * k + i].x, b[3 * k + i].y);
#pragma unroll
                for (int i = 0; i < 3; i++) mma(c[i], f[2 * i + 1], b[3 * k + i].z, b[3 * k + i].w);
            }
            asm volatile("{\n.reg .pred p;\nsetp.eq.u32 p, %3, 0;\n@p st.shared.f32 [%0], %1;\n@p st.shared.f32 [%0 + 256], %2;\n}"
                         :: "r"(part), "f"(c[0][0] + c[1][0] + c[2][0]), "f"(c[0][2] + c[1][2] + c[2][2]), "r"(quad) : "memory");
            __syncwarp();
            if (lane == 0) mbar_arrive(sm + kOffPartBar);
        } else if (w == 8) {
            uint32_t part = sm + kOffPart + (lane & 15) * 32;
            pin(part);
            for (unsigned n = 0; !mbar_test(sm + kOffPartBar, pass); n++) if (n > kSpinLimit) __trap();
            const uint4 p0 = lds128(part), p1 = lds128(part + 16);
            const float d = ((__uint_as_float(p0.x) + __uint_as_float(p0.y)) + (__uint_as_float(p0.z) + __uint_as_float(p0.w))) +
                            ((__uint_as_float(p1.x) + __uint_as_float(p1.y)) + (__uint_as_float(p1.z) + __uint_as_float(p1.w)));
            asm volatile("st.volatile.shared.u32 [%0], %1;" :: "r"(sm + kOffGate + (lane & 15) * 4),
                         "r"((__float_as_uint(bf16r(silu(bf16r(d)))) & ~1u) | pass) : "memory");
        } else {
            const uint4 trip = lds128(sm + kOffTrip);
            const int col = (lane & 15) / 2 + 8 * (lane & 1);
            uint32_t* src = box_pair(kCtas + fin) + (trip.w < trip.z ? kCopy : 0) + lane;
            __nv_bfloat16* res = (pass ? out + 16 * fin : reinterpret_cast<__nv_bfloat16*>(g_sink)) + col;
            uint32_t gate = sm + kOffGate + col * 4, g;
            pin(src); pin(res); pin(gate);
            uint32_t v[16];
#pragma unroll
            for (int i = 0; i < 16; i++) v[i] = pass ^ 1;
            if (!pass) tag = 1;
            for (unsigned n = 0; !mbar_test(full + 8 * kSlotDown, parity) && pass; n++) if (n > kSpinLimit) __trap();
            for (unsigned n = 0;; n++) {
#pragma unroll
                for (int i = 0; i < 16; i++) peek(src + 32 * i, v[i], tag);
                asm volatile("ld.volatile.shared.u32 %0, [%1];" : "=r"(g) : "r"(gate) : "memory");
                uint32_t have = tag;
#pragma unroll
                for (int i = 0; i < 16; i++) have &= v[i];
                if (__all_sync(~0u, have)) break;
                if (n > kSpinLimit) __trap();
            }
            float sum[8];
#pragma unroll
            for (int i = 0; i < 8; i++) sum[i] = __uint_as_float(v[i]) + __uint_as_float(v[i + 8]);
            float s = ((sum[0] + sum[1]) + (sum[2] + sum[3])) + ((sum[4] + sum[5]) + (sum[6] + sum[7]));
            s = bf16r(s + __shfl_xor_sync(~0u, s, 16));
            for (unsigned n = 0; !(g & 1) && pass; n++) {
                asm volatile("ld.volatile.shared.u32 %0, [%1];" : "=r"(g) : "r"(gate) : "memory");
                if (n > kSpinLimit) __trap();
            }
            *res = __float2bfloat16_rn(xin + bf16r(s * untagged(g)));
        }
    }
}

__global__ void __launch_bounds__(kThreads, 1)
decode_block_kernel(const uint8_t* __restrict__ wq_bytes, const __nv_bfloat16* __restrict__ x, __nv_bfloat16* __restrict__ out,
                    const __grid_constant__ Maps maps) {
    if (threadIdx.x < 4 * 48) {
        constexpr int kPitch = kH * kDh * 2;
        const uint8_t* line = wq_bytes + ((160 * (blockIdx.x & 3) * kPitch + (blockIdx.x >> 2) * (kDh * 2)) +
                                          (threadIdx.x >> 2) * kPitch + (threadIdx.x & 3) * 128);
        asm volatile("prefetch.global.L2 [%0];" :: "l"(line) : "memory");
    }
    extern __shared__ __align__(1024) uint8_t smem[];
    const uint32_t sm = (uint32_t)__cvta_generic_to_shared(smem);
    const int w = threadIdx.x >> 5;
    const int h = blockIdx.x >> 2, j = blockIdx.x & 3;
    uint64_t pol;
    asm volatile("createpolicy.fractional.L2::evict_first.b64 %0, 1.0;" : "=l"(pol));
    uint32_t sm0 = sm;
    const CUtensorMap* wq = &maps.wq;
    pin(sm0);
    pin(wq);
    if (threadIdx.x == 128) {
        first_loads(wq, sm0, h, j, pol);
#pragma unroll
        for (int i = 0; i < kStages; i++) {
            if (i >= kLdGate) mbar_init(sm + kOffBar + 8 * i, 1);
            mbar_init(sm + kOffBar + 8 * (kStages + i), 5);
        }
        mbar_init(sm + kOffVecBar, 4);
        mbar_init(sm + kOffPartBar, 8);
        asm volatile("fence.mbarrier_init.release.cluster;" ::: "memory");
    }
    __syncwarp();
    if (w == 4) {
        bar_arrive<kBarMonitor, 64>();
        bar_arrive<kBarInit, 480>();
        if (threadIdx.x == 128) producer(maps, sm, h, j, pol);
    } else if (w == 5) {
        bar_sync<kBarMonitor, 64>();
        if (threadIdx.x == 160) monitor(sm, h);
    } else if (w < 4) {
        consumer(x, smem, sm, j);
    } else {
        projector(x, out, smem, sm, h, j);
    }
}

typedef CUresult (*EncodeFn)(CUtensorMap*, CUtensorMapDataType, cuuint32_t, void*, const cuuint64_t*, const cuuint64_t*,
                             const cuuint32_t*, const cuuint32_t*, CUtensorMapInterleave, CUtensorMapSwizzle,
                             CUtensorMapL2promotion, CUtensorMapFloatOOBfill);

void encode3(EncodeFn enc, CUtensorMap* tm, const void* p, uint64_t rows, uint64_t cols, uint32_t inner, uint32_t segs,
             uint32_t box_rows, CUtensorMapSwizzle sw,
             CUtensorMapL2promotion promo = CU_TENSOR_MAP_L2_PROMOTION_NONE) {
    const cuuint64_t dims[3] = {inner, cols / inner, rows};
    const cuuint64_t strides[2] = {inner * 2ull, cols * 2ull};
    const cuuint32_t box[3] = {inner, segs, box_rows};
    const cuuint32_t es[3] = {1, 1, 1};
    enc(tm, CU_TENSOR_MAP_DATA_TYPE_BFLOAT16, 3, const_cast<void*>(p), dims, strides, box, es,
        CU_TENSOR_MAP_INTERLEAVE_NONE, sw, promo, CU_TENSOR_MAP_FLOAT_OOB_FILL_NONE);
}

}

extern "C" void kernel_launch(void* const* d_in, const int* in_sizes, int n_in, void* d_out, int out_size) {
    (void)in_sizes; (void)n_in; (void)out_size;
    static EncodeFn enc = nullptr;
    if (!enc) {
        void* fn = nullptr;
        cudaDriverEntryPointQueryResult qr;
        cudaGetDriverEntryPoint("cuTensorMapEncodeTiled", &fn, cudaEnableDefault, &qr);
        enc = (EncodeFn)fn;
        cudaFuncSetAttribute(decode_block_kernel, cudaFuncAttributeMaxDynamicSharedMemorySize, kSmemBytes);
    }
    Maps maps;
    encode3(enc, &maps.k, d_in[1], (uint64_t)kH * kSk, kDh, 64, 3, 64, CU_TENSOR_MAP_SWIZZLE_128B);
    encode3(enc, &maps.v, d_in[2], (uint64_t)kH * kSk, kDh, 64, 3, 64, CU_TENSOR_MAP_SWIZZLE_128B);
    encode3(enc, &maps.wq, d_in[3], kD, kH * kDh, 64, 3, 64, CU_TENSOR_MAP_SWIZZLE_128B);
    encode3(enc, &maps.wq_tail, d_in[3], kD, kH * kDh, 64, 3, 32, CU_TENSOR_MAP_SWIZZLE_128B);
    encode3(enc, &maps.wo, d_in[4], kH * kDh, kD, 32, 5, 64, CU_TENSOR_MAP_SWIZZLE_64B);
    encode3(enc, &maps.gate, d_in[6], kD, kF, 48, 1, 160, CU_TENSOR_MAP_SWIZZLE_NONE);
    encode3(enc, &maps.up, d_in[7], kD, kF, 48, 1, 160, CU_TENSOR_MAP_SWIZZLE_NONE);
    encode3(enc, &maps.down, d_in[8], kF, kD, 16, 1, 256, CU_TENSOR_MAP_SWIZZLE_32B, CU_TENSOR_MAP_L2_PROMOTION_L2_256B);
    decode_block_kernel<<<kCtas, kThreads, kSmemBytes>>>(
        (const uint8_t*)d_in[3], (const __nv_bfloat16*)d_in[0], (__nv_bfloat16*)d_out, maps);
}
```
